```python
import torch

def _softmax(x, axis=-1):
    return torch.softmax(x, dim=axis)
def _gelu(x):
    return torch.nn.functional.gelu(x, approximate="tanh")
def _silu(x):
    return torch.nn.functional.silu(x)
def _sigmoid(x):
    return torch.sigmoid(x)
def _layernorm(x, axis=-1, eps=1e-5):
    m = x.mean(dim=axis, keepdim=True)
    v = x.var(dim=axis, keepdim=True, unbiased=False)
    return (x - m) / torch.sqrt(v + eps)
def _scatter_add(tgt, idx, src, axis=0):
    return tgt.clone().index_add_(axis, idx, src)
def _segment_sum(src, seg, n):
    out = torch.zeros((n,) + src.shape[1:], dtype=src.dtype)
    return out.index_add_(0, seg, src)
def _pad(x, pw):
    flat = tuple(v for pair in reversed(pw) for v in pair)
    return torch.nn.functional.pad(x, flat)

kernel_name = 'sequential_preLN__gqa_block_cached__glu_gated_swiglu__decode'

def setup_inputs():

    _w = (lambda a: (lambda t: t.to(torch.bfloat16) if t.is_floating_point() else t)(torch.as_tensor(a)))
    def _A_setup():
        B, Sq, D = 2, 1, 576
        Hq, Hkv, Sk, Dh = 32, 16, 32768, 128
        assert Hq % Hkv == 0, (Hq, Hkv)
        return {
            "x": _w((lambda *s: torch.randn(*s, dtype=torch.bfloat16) * 0.05)(B, Sq, D)),
            "k_cache": _w((lambda *s: torch.randn(*s, dtype=torch.bfloat16) * 3.2)(B, Hkv, Sk, Dh)),
            "v_cache": _w((lambda *s: torch.randn(*s, dtype=torch.bfloat16) * 1.6)(B, Hkv, Sk, Dh)),
            "wq": _w((lambda *s: torch.randn(*s, dtype=torch.bfloat16) * 3.2)(D, Hq * Dh) * (D ** -0.5)),
            "wo": _w((lambda *s: torch.randn(*s, dtype=torch.bfloat16) * 1.6)(Hq * Dh, D) * ((Hq * Dh) ** -0.5)),
        }
    _A_in = _A_setup()

    def _B_setup():
        B, S, D, F = 2, 1, 576, 4608
        return {
            "x": _w((lambda *s: torch.randn(*s, dtype=torch.bfloat16) * 0.05)(B, S, D)),
            "w1": _w((lambda *s: torch.randn(*s, dtype=torch.bfloat16) * 1.6)(D, F) * (2.0 / D) ** 0.5),
            "w3": _w((lambda *s: torch.randn(*s, dtype=torch.bfloat16) * 1.6)(D, F) * (2.0 / D) ** 0.5),
            "w2": _w((lambda *s: torch.randn(*s, dtype=torch.bfloat16) * 1.6)(F, D) * (2.0 / F) ** 0.5),
        }
    _B_in = _B_setup()

    return {
        "A_x": _A_in["x"],
        "A_k_cache": _A_in["k_cache"],
        "A_v_cache": _A_in["v_cache"],
        "A_wq": _A_in["wq"],
        "A_wo": _A_in["wo"],
        "B_x": _B_in["x"],
        "B_w1": _B_in["w1"],
        "B_w3": _B_in["w3"],
        "B_w2": _B_in["w2"],
    }

def reference(A_x, A_k_cache, A_v_cache, A_wq, A_wo, B_x, B_w1, B_w3, B_w2):
    def _A_ref(x, k_cache, v_cache, wq, wo):
        B, Sq, D = x.shape
        Hq, Dh = 32, 128
        Hkv = k_cache.shape[1]
        rep = Hq // Hkv
        q = (lambda x, *d: x.permute(*d))((x @ wq).reshape(B, Sq, Hq, Dh), 0, 2, 1, 3)
        k = (lambda x, n, axis: torch.repeat_interleave(x, n, dim=axis))(k_cache, rep, axis=1)
        v = (lambda x, n, axis: torch.repeat_interleave(x, n, dim=axis))(v_cache, rep, axis=1)
        scores = torch.einsum("bhqd,bhkd->bhqk", q, k) * (Dh ** -0.5)
        p = _softmax(scores, axis=-1)
        o = torch.einsum("bhqk,bhkd->bhqd", p, v)
        return (lambda x, *d: x.permute(*d))(o, 0, 2, 1, 3).reshape(B, Sq, Hq * Dh) @ wo

    def _B_ref(x, w1, w3, w2):
        gate = torch.einsum("bsd,df->bsf", x, w1)
        up = torch.einsum("bsd,df->bsf", x, w3)
        h = _silu(gate) * up
        out = torch.einsum("bsf,fd->bsd", h, w2)
        return out

    x = A_x
    h = x + _A_ref(_layernorm(x, axis=-1), A_k_cache, A_v_cache, A_wq, A_wo)
    h2 = h + _B_ref(_layernorm(h, axis=-1), B_w1, B_w3, B_w2)
    return h2
```

```cpp
#include <cuda_runtime.h>
#include <cuda_bf16.h>
#include <cuda.h>
#include <stdint.h>

#define DBG_TIMELINE 0

namespace {

constexpr int D_MODEL = 576;
constexpr int HKV = 16;
constexpr int SK = 32768;
constexpr int QDIM = 4096;
constexpr int FF = 4608;

constexpr int NCTA = 128;
constexpr int NTHREADS = 384;
constexpr int TILE_KEYS = 64;
constexpr int NTILES = SK / 4 / TILE_KEYS;
constexpr int SLOT_BYTES = TILE_KEYS * 256;
constexpr int NSLOTS = 8;
constexpr int NKV = 2 * NTILES;
constexpr int NRED = 72;

#define DEPTH_START 4
#define DEPTH_MAIN 4
#define DEPTH_END 3
#define START_LOADS 4
#define DBG_SKIP 0
#define W_PROMO CU_TENSOR_MAP_L2_PROMOTION_L2_128B
#define PF_MODE 0
#define DEPTH_MIN 3
#define PACE_BIAS 0
#define PACE_SHIFT 8
#define MON_SLEEP 1000
#define CLEAR_AT 0
#define PROBES 3
#define DEPTH_QUIET 3
#define GRP_MAP 1
#define CHUNK_LOG 1
#define SKEW 0
#define HELP_SLEEP 200
#define B0_LAG 32
#define Q_SLEEP 800
#define P1_HINT 1
#define HOME_MODE 1

#define LATE_W1 4
#define P4_DELAY 0
constexpr int WQ_PIECE = 144 * 64;
constexpr int W13_PIECE = 144 * 80;
constexpr int ROW8_PIECE = 8 * 1152;

constexpr int SM_RING = 0;
constexpr int SM_WO = NSLOTS * SLOT_BYTES;
constexpr int SM_W1 = SM_WO + 4 * ROW8_PIECE;
constexpr int SM_W2 = SM_RING + 4 * SLOT_BYTES;
constexpr int SM_BAR = SM_W1 + 4 * W13_PIECE;
constexpr int SM_RED = SM_BAR + 320;
constexpr int SM_XN = SM_RED + 4096;
constexpr int XN_PITCH = 584 * 2;
constexpr int SM_ML = SM_RED + 8 * 88 * 16;
constexpr int SM_Q = SM_ML + 64;
constexpr int SM_ACT = SM_Q + 1024;
constexpr int SM_RED2 = SM_ACT + 192;
constexpr int SM_RED4 = SM_RED2 + 128;
constexpr int SM_PX = SM_RED4 + 512;
constexpr int SM_HS = SM_PX + 2048;
constexpr int SM_ONES = SM_HS + 8 * 18 * 16;
constexpr int SM_HRES = SM_ONES + 16;
constexpr int SM_PROG = SM_HRES + 32;
constexpr int SM_HOME = SM_PROG + 16;
constexpr int SM_TOTAL = SM_HOME + 144;
static_assert(SM_TOTAL <= 232448, "smem");

constexpr unsigned SENTINEL = 0xFFFFFFFFu;
constexpr float LOG2E = 1.4426950408889634f;
constexpr float SCALE = 0.08838834764831845f;
constexpr unsigned SPIN_LIMIT = 1u << 24;

}

__device__ __align__(128) unsigned g_sync[3 * 32];
__device__ __align__(128) uint2 g_pq[2][HKV][128];
constexpr uint32_t X_P3 = 0, X_P1 = 8 * 8192, X_P2 = 72 * 8192, X_P4 = 144 * 8192, X_PR = 216 * 8192, X_END = 232 * 8192;
static_assert(X_END <= (2u << 20), "one page");
__device__ unsigned char g_xraw[(2u << 20) + X_END];
__device__ __align__(128) unsigned g_home[NCTA];
__device__ __forceinline__ uint32_t near_of(uint32_t blk, uint32_t side) { return blk + (((__popc(blk & 0xB2000u) ^ side) & 1) << 12); }
#define TL(i) do {} while (0)
#define TLCAL(i) do {} while (0)
#define TLM(i) do {} while (0)

__device__ __forceinline__ void mbar_init(uint32_t bar, uint32_t cnt) {
    asm volatile("mbarrier.init.shared::cta.b64 [%0], %1;" ::"r"(bar), "r"(cnt) : "memory");
}
__device__ __forceinline__ void mbar_expect_tx(uint32_t bar, uint32_t bytes) {
    asm volatile("mbarrier.arrive.expect_tx.shared::cta.b64 _, [%0], %1;" ::"r"(bar), "r"(bytes) : "memory");
}
__device__ __forceinline__ void mbar_arrive(uint32_t bar) {
    asm volatile("mbarrier.arrive.shared::cta.b64 _, [%0];" ::"r"(bar) : "memory");
}
__device__ __forceinline__ void mbar_wait(uint32_t bar, uint32_t parity) {
    asm volatile("{\n.reg .pred p;\n.reg .u32 n;\nmov.u32 n, 0;\n"
                 "WAIT_LOOP:\nmbarrier.try_wait.parity.shared::cta.b64 p, [%0], %1;\n@p bra WAIT_DONE;\n"
                 "add.u32 n, n, 1;\nsetp.lt.u32 p, n, 0x1000000;\n@p bra WAIT_LOOP;\ntrap;\nWAIT_DONE:\n}"
                 ::"r"(bar), "r"(parity) : "memory");
}
__device__ __forceinline__ void bar_sync(int id, int n) { asm volatile("bar.sync %0, %1;" ::"r"(id), "r"(n) : "memory"); }
__device__ __forceinline__ void bar_arrive(int id, int n) { asm volatile("bar.arrive %0, %1;" ::"r"(id), "r"(n) : "memory"); }

__device__ __forceinline__ void tma2d(uint32_t dst, const CUtensorMap* m, int c0, int c1, uint32_t bar) {
    asm volatile("cp.async.bulk.tensor.2d.shared::cluster.global.mbarrier::complete_tx::bytes [%0], [%1, {%3, %4}], [%2];"
                 ::"r"(dst), "l"(m), "r"(bar), "r"(c0), "r"(c1) : "memory");
}
__device__ __forceinline__ void tma3d(uint32_t dst, const CUtensorMap* m, int c1, uint32_t bar) {
    asm volatile("cp.async.bulk.tensor.3d.shared::cluster.global.mbarrier::complete_tx::bytes [%0], [%1, {0, %3, 0}], [%2];"
                 ::"r"(dst), "l"(m), "r"(bar), "r"(c1) : "memory");
}
__device__ __forceinline__ void tma3d_hint(uint32_t dst, const CUtensorMap* m, int c1, uint32_t bar, uint64_t pol) {
    asm volatile("cp.async.bulk.tensor.3d.shared::cluster.global.mbarrier::complete_tx::bytes.L2::cache_hint [%0], [%1, {0, %3, 0}], [%2], %4;"
                 ::"r"(dst), "l"(m), "r"(bar), "r"(c1), "l"(pol) : "memory");
}
__device__ __forceinline__ void ldsm4(uint32_t (&r)[4], uint32_t a) {
    asm volatile("ldmatrix.sync.aligned.m8n8.x4.shared.b16 {%0,%1,%2,%3}, [%4];"
                 : "=r"(r[0]), "=r"(r[1]), "=r"(r[2]), "=r"(r[3]) : "r"(a) : "memory");
}
__device__ __forceinline__ void ldsm4t(uint32_t (&r)[4], uint32_t a) {
    asm volatile("ldmatrix.sync.aligned.m8n8.x4.trans.shared.b16 {%0,%1,%2,%3}, [%4];"
                 : "=r"(r[0]), "=r"(r[1]), "=r"(r[2]), "=r"(r[3]) : "r"(a) : "memory");
}
__device__ __forceinline__ void ldsm2t(uint32_t& r0, uint32_t& r1, uint32_t a) {
    asm volatile("ldmatrix.sync.aligned.m8n8.x2.trans.shared.b16 {%0,%1}, [%2];" : "=r"(r0), "=r"(r1) : "r"(a) : "memory");
}
__device__ __forceinline__ void ldsm1t(uint32_t& r0, uint32_t a) {
    asm volatile("ldmatrix.sync.aligned.m8n8.x1.trans.shared.b16 {%0}, [%1];" : "=r"(r0) : "r"(a) : "memory");
}
__device__ __forceinline__ void ldsm1(uint32_t& r0, uint32_t a) {
    asm volatile("ldmatrix.sync.aligned.m8n8.x1.shared.b16 {%0}, [%1];" : "=r"(r0) : "r"(a) : "memory");
}
__device__ __forceinline__ void mma16816(float (&c)[4], uint32_t a0, uint32_t a1, uint32_t a2, uint32_t a3, uint32_t b0, uint32_t b1) {
    asm("mma.sync.aligned.m16n8k16.row.col.f32.bf16.bf16.f32 {%0,%1,%2,%3}, {%4,%5,%6,%7}, {%8,%9}, {%0,%1,%2,%3};"
                 : "+f"(c[0]), "+f"(c[1]), "+f"(c[2]), "+f"(c[3]) : "r"(a0), "r"(a1), "r"(a2), "r"(a3), "r"(b0), "r"(b1));
}
__device__ __forceinline__ void mma16816v(float (&c)[4], uint32_t a0, uint32_t a1, uint32_t a2, uint32_t a3, uint32_t b0, uint32_t b1) {
    asm volatile("mma.sync.aligned.m16n8k16.row.col.f32.bf16.bf16.f32 {%0,%1,%2,%3}, {%4,%5,%6,%7}, {%8,%9}, {%0,%1,%2,%3};"
                 : "+f"(c[0]), "+f"(c[1]), "+f"(c[2]), "+f"(c[3]) : "r"(a0), "r"(a1), "r"(a2), "r"(a3), "r"(b0), "r"(b1));
}
__device__ __forceinline__ float4 lds128(uint32_t a) {
    float4 v;
    asm volatile("ld.shared.v4.f32 {%0,%1,%2,%3}, [%4];" : "=f"(v.x), "=f"(v.y), "=f"(v.z), "=f"(v.w) : "r"(a) : "memory");
    return v;
}
__device__ __forceinline__ void sts64(uint32_t a, float x, float y) {
    asm volatile("st.shared.v2.f32 [%0], {%1,%2};" ::"r"(a), "f"(x), "f"(y) : "memory");
}
__device__ __forceinline__ void mma1688(float (&c)[4], uint32_t a0, uint32_t a1, uint32_t b0) {
    asm("mma.sync.aligned.m16n8k8.row.col.f32.bf16.bf16.f32 {%0,%1,%2,%3}, {%4,%5}, {%6}, {%0,%1,%2,%3};"
                 : "+f"(c[0]), "+f"(c[1]), "+f"(c[2]), "+f"(c[3]) : "r"(a0), "r"(a1), "r"(b0));
}
__device__ __forceinline__ uint32_t movm(uint32_t a) {
    uint32_t d;
    asm volatile("movmatrix.sync.aligned.m8n8.trans.b16 %0, %1;" : "=r"(d) : "r"(a));
    return d;
}
__device__ __forceinline__ uint32_t pack_bf16(float lo, float hi) {
    uint32_t d;
    asm("cvt.rn.bf16x2.f32 %0, %1, %2;" : "=r"(d) : "f"(hi), "f"(lo));
    return d;
}
__device__ __forceinline__ float bf_lo(uint32_t v) { return __uint_as_float(v << 16); }
__device__ __forceinline__ float bf_hi(uint32_t v) { return __uint_as_float(v & 0xFFFF0000u); }
__device__ __forceinline__ float bfr(float x) { return __bfloat162float(__float2bfloat16_rn(x)); }
__device__ __forceinline__ float ex2(float x) { float y; asm("ex2.approx.ftz.f32 %0, %1;" : "=f"(y) : "f"(x)); return y; }
__device__ __forceinline__ float rcp(float x) { float y; asm("rcp.approx.ftz.f32 %0, %1;" : "=f"(y) : "f"(x)); return y; }
__device__ __forceinline__ float lg2(float x) { float y; asm("lg2.approx.ftz.f32 %0, %1;" : "=f"(y) : "f"(x)); return y; }

__device__ __forceinline__ uint4 ld_relaxed128(const void* p) {
    uint4 v;
    asm volatile("{\n.reg .b128 t;\n.reg .b64 lo, hi;\nld.relaxed.gpu.global.b128 t, [%4];\nmov.b128 {lo, hi}, t;\n"
                 "mov.b64 {%0, %1}, lo;\nmov.b64 {%2, %3}, hi;\n}"
                 : "=r"(v.x), "=r"(v.y), "=r"(v.z), "=r"(v.w) : "l"(p) : "memory");
    return v;
}
__device__ __forceinline__ void st_relaxed128(void* p, uint32_t x, uint32_t y, uint32_t z, uint32_t w) {
    asm volatile("{\n.reg .b128 t;\n.reg .b64 lo, hi;\nmov.b64 lo, {%1, %2};\nmov.b64 hi, {%3, %4};\nmov.b128 t, {lo, hi};\n"
                 "st.relaxed.gpu.global.b128 [%0], t;\n}"
                 ::"l"(p), "r"(x), "r"(y), "r"(z), "r"(w) : "memory");
}
__device__ __forceinline__ uint2 ld_relaxed64(const void* p) {
    uint2 v;
    asm volatile("{\n.reg .b64 t;\nld.relaxed.gpu.global.b64 t, [%2];\nmov.b64 {%0, %1}, t;\n}" : "=r"(v.x), "=r"(v.y) : "l"(p) : "memory");
    return v;
}
__device__ __forceinline__ void st_relaxed64(void* p, uint32_t x, uint32_t y) {
    asm volatile("{\n.reg .b64 t;\nmov.b64 t, {%1, %2};\nst.relaxed.gpu.global.b64 [%0], t;\n}" ::"l"(p), "r"(x), "r"(y) : "memory");
}
__device__ __forceinline__ unsigned ld_relaxed32(const void* p) {
    unsigned v;
    asm volatile("ld.relaxed.gpu.global.u32 %0, [%1];" : "=r"(v) : "l"(p) : "memory");
    return v;
}
__device__ __forceinline__ void st_relaxed32(void* p, unsigned v) {
    asm volatile("st.relaxed.gpu.global.u32 [%0], %1;" ::"l"(p), "r"(v) : "memory");
}
__device__ __forceinline__ void red_add(unsigned* p) {
    asm volatile("red.relaxed.gpu.global.add.u32 [%0], 1;" ::"l"(p) : "memory");
}
__device__ __forceinline__ bool valid4(const uint4& v) {
    return v.x != SENTINEL && v.y != SENTINEL && v.z != SENTINEL && v.w != SENTINEL;
}
__device__ __forceinline__ uint32_t not_sentinel(uint32_t u) { return u == SENTINEL ? 0x7FFF7FFFu : u; }
__device__ __forceinline__ uint4 ldg_nc128(const void* p) {
    uint4 v;
    asm volatile("ld.global.nc.L1::no_allocate.v4.u32 {%0,%1,%2,%3}, [%4];" : "=r"(v.x), "=r"(v.y), "=r"(v.z), "=r"(v.w) : "l"(p));
    return v;
}

__device__ __forceinline__ unsigned near_page(unsigned* p) {
    unsigned best0, best1;
    asm volatile("atom.relaxed.gpu.global.exch.b32 %0, [%1], 0;" : "=r"(best0) : "l"(p) : "memory");
    asm volatile("atom.relaxed.gpu.global.exch.b32 %0, [%1], 0;" : "=r"(best1) : "l"(p + 1024) : "memory");
    asm volatile("or.b32 %0, %0, 0x7fffffff;" : "+r"(best0) :: "memory");
    asm volatile("or.b32 %0, %0, 0x7fffffff;" : "+r"(best1) :: "memory");
#pragma unroll 1
    for (int i = 0; i < 2 * PROBES; i++) {
        unsigned v, t0, t1;
        asm volatile("mov.u32 %0, %%clock;" : "=r"(t0) :: "memory");
        asm volatile("atom.relaxed.gpu.global.exch.b32 %0, [%1], %2;" : "=r"(v) : "l"(p + ((i & 1) << 10)), "r"(SENTINEL) : "memory");
        asm volatile("{\n.reg .pred p;\nsetp.ne.u32 p, %1, 0x5a5a5a5a;\nmov.u32 %0, 0;\n@p mov.u32 %0, %%clock;\n}" : "=r"(t1) : "r"(v) : "memory");
        if (i & 1) best1 = min(best1, t1 - t0); else best0 = min(best0, t1 - t0);
    }
    return HOME_MODE == 1 ? best1 < best0 : HOME_MODE == 2 ? best1 >= best0 : 0;
}

enum { BAR_ALL = 1, BAR_MAIN = 2, BAR_HELP = 3, BAR_RDY = 4, BAR_INIT = 5, BAR_PROBE = 6, BAR_F1 = 7, BAR_ACT = 8 };
#define PIN(v) asm volatile("" : "+r"(v))

__global__ void __launch_bounds__(NTHREADS, 1)
fused_decode_kernel(const __grid_constant__ CUtensorMap map_k, const __grid_constant__ CUtensorMap map_v,
                    const __grid_constant__ CUtensorMap map_wo, const __grid_constant__ CUtensorMap map_w1,
                    const __grid_constant__ CUtensorMap map_w3, const __grid_constant__ CUtensorMap map_w2,
                    const __grid_constant__ CUtensorMap map_wq, const __nv_bfloat16* __restrict__ x,
                    __nv_bfloat16* __restrict__ out) {
    extern __shared__ __align__(1024) unsigned char smem[];
    const uint32_t sb = (uint32_t)__cvta_generic_to_shared(smem);
    const int tid = threadIdx.x, lane = tid & 31;
    const int warp = __shfl_sync(0xffffffffu, tid >> 5, 0);
    const int cta = blockIdx.x;
    const int hkv = GRP_MAP ? cta & 15 : cta >> 3, r = GRP_MAP ? cta >> 4 : cta & 7;
    const uint32_t bar_full = sb + SM_BAR, bar_empty = bar_full + 64, bar_w = bar_full + 128,
                   bar_l = bar_full + 192;
    volatile int* const prog = reinterpret_cast<volatile int*>(smem + SM_PROG);
    float* const red = reinterpret_cast<float*>(smem + SM_RED);
    unsigned char* const g_x = reinterpret_cast<unsigned char*>((reinterpret_cast<uintptr_t>(g_xraw) + 0x1FFFFF) & ~(uintptr_t)0x1FFFFF);

    if (warp == 8) {
        if (lane == 0) TL(0);
        const int f0 = (cta >> 1) * 72 + (cta & 1) * 32;
        const int c0 = hkv * 256 + r * 32;
        if (lane == 0) {
#pragma unroll
            for (int p = 0; p < 8; p++) mbar_init(bar_w + 8 * p, 1);
#pragma unroll
            for (int p = 0; p < 4; p++) {
                mbar_expect_tx(bar_w + 8 * p, WQ_PIECE);
                tma2d(sb + SM_W1 + p * WQ_PIECE, &map_wq, c0, p * 144, bar_w + 8 * p);
            }
        }
        __syncwarp();
        bar_arrive(0, 320);
        bar_sync(BAR_INIT, 64);
        if (lane == 0) {
            uint64_t pol;
            asm volatile("createpolicy.fractional.L2::evict_first.b64 %0, 1.0;" : "=l"(pol));
#pragma unroll 1
            for (int p = 4; p < 8; p++) {
                const uint32_t bar = bar_w + 8 * p;
                if (p >= DEPTH_START) mbar_wait(bar - 8 * DEPTH_START, 0);
                mbar_expect_tx(bar, ROW8_PIECE);
                tma3d(sb + SM_WO + (p - 4) * ROW8_PIECE, &map_wo, c0 + (p - 4) * 8, bar);
            }
            const int row0 = hkv * SK + r * (TILE_KEYS << CHUNK_LOG);
#pragma unroll 1
            for (int i = 0; i < NKV; i++) {
                const int slot = i & (NSLOTS - 1);
                if (i >= NSLOTS) mbar_wait(bar_empty + 8 * slot, ((i >> 3) - 1) & 1);
                const int j = i - (i < START_LOADS ? DEPTH_QUIET : prog[1]);
                if (j >= 0) mbar_wait(bar_full + 8 * (j & 7), (j >> 3) & 1);
                else mbar_wait(bar_w + 8 * (8 + j), 0);
                prog[0] = j + 1;
                const int tt = (((i >> 1) + SKEW * (hkv + 16 * (i & 1) * 0)) & 63);
                const int row = (DBG_SKIP & 256) ? ((r >> 2) * HKV + hkv) * SK + (r & 3) * 128 + (i >> 2) * 512 + ((i >> 1) & 1) * 64 : row0 + (i >> 7) * (HKV * SK) + (tt >> CHUNK_LOG) * ((8 * TILE_KEYS) << CHUNK_LOG) + (tt & ((1 << CHUNK_LOG) - 1)) * TILE_KEYS;
                mbar_expect_tx(bar_full + 8 * slot, SLOT_BYTES);
                tma3d_hint(sb + SM_RING + slot * SLOT_BYTES, (i & 1) ? &map_v : &map_k, row, bar_full + 8 * slot, pol);
                if (i >= 32 && i < 32 + 4 - LATE_W1) {
                    mbar_expect_tx(bar_l + 8 * slot, W13_PIECE);
                    tma2d(sb + SM_W1 + slot * W13_PIECE, &map_w1, f0, slot * 144, bar_l + 8 * slot);
                }
                if (i == NKV - 32) {
                    asm volatile("prefetch.tensormap [%0];" ::"l"(&map_w1) : "memory");
                    asm volatile("prefetch.tensormap [%0];" ::"l"(&map_w3) : "memory");
                    asm volatile("prefetch.tensormap [%0];" ::"l"(&map_w2) : "memory");
                }
            }
            TL(1);
            prog[0] = NKV;
#pragma unroll 1
            for (int p = 4 - LATE_W1; p < 13; p++) {
                const uint32_t bar = bar_l + 8 * p;
                const int j = p - DEPTH_END;
                if (j >= 4 - LATE_W1) mbar_wait(bar_l + 8 * j, 0);
                else mbar_wait(bar_full + 8 * ((j - 4 + LATE_W1) & 7), 1);
                if (p >= 4 && p < 11) mbar_wait(bar_empty + 8 * (p - 4), 1);
                if (((DBG_SKIP & 2) && p < 4) || ((DBG_SKIP & 4) && p >= 4 && p < 8) || ((DBG_SKIP & 8) && p >= 8) || (p == 8 && (cta & 1))) {
                    mbar_arrive(bar);
                } else if (p < 8) {
                    mbar_expect_tx(bar, W13_PIECE);
                    tma2d(sb + (p < 4 ? SM_W1 + p * W13_PIECE : SM_RING + (p - 4) * SLOT_BYTES), p < 4 ? &map_w1 : &map_w3, f0, (p & 3) * 144, bar);
                } else {
                    mbar_expect_tx(bar, ROW8_PIECE);
                    tma3d(sb + SM_W2 + (p - 8) * ROW8_PIECE, &map_w2, f0 + (p - 8) * 8, bar);
                }
            }
            TL(2);
        }
        return;
    }

    if (warp > 8) {
        if (warp == 9) {
            if (lane == 0) {
#pragma unroll
                for (int i = 0; i < 16; i++) mbar_init(bar_full + 8 * i, i < 8 ? 1 : 4);
#pragma unroll
                for (int i = 0; i < 13; i++) mbar_init(bar_l + 8 * i, 1);
                prog[0] = 0; prog[1] = DEPTH_MAIN;
                *reinterpret_cast<uint4*>(smem + SM_ONES) = make_uint4(0x3F803F80u, 0x3F803F80u, 0x3F803F80u, 0x3F803F80u);
            }
            __syncwarp();
            bar_arrive(BAR_INIT, 64);
            bar_arrive(0, 320);
        }
        if (lane == 0) {
            const uint32_t blk = X_PR + (cta & 15) * 8192;
            smem[SM_HOME + 128 + warp - 9] = (near_page(reinterpret_cast<unsigned*>(g_x + blk + (cta >> 4) * 512 + (warp - 9) * 128)) ^ __popc(blk & 0xB2000u)) & 1;
            if (warp == 10) TL(26);
        }
        __syncwarp();
        bar_arrive(BAR_PROBE, 224);
        if (warp == 9) {
            if (lane == 0) {
                TLCAL(30);
                int last = 0, cur;
                unsigned n = 0;
                do {
                    if (++n > SPIN_LIMIT) __trap();
                    __nanosleep(MON_SLEEP);
                    cur = prog[0];
                    const int tot = (int)atomicAdd(&g_sync[64], (unsigned)(cur - last));
                    last = cur;
                    const int lead = cur * NCTA - tot - PACE_BIAS;
                    prog[1] = max(DEPTH_MIN, min(NSLOTS, DEPTH_MAIN - (lead >> PACE_SHIFT)));
                } while (cur < NKV - 8);
                TLCAL(28);
            }
            __syncwarp();
        }
        const int at = tid - 288, bb = at & 1;
        uint32_t ra = sb + SM_RED + min(at, 79) * 16, rs = sb + SM_RED + (80 + bb) * 16;
        uint32_t wa = sb + SM_ACT + bb * 80 + (at >> 1) * 2;
        PIN(ra); PIN(rs); PIN(wa);
        bar_sync(BAR_F1, 352);
        float v0 = 0.f, v1 = 0.f, cs = 0.f, sq = 0.f, sm = 0.f;
#pragma unroll
        for (int wv = 0; wv < 8; wv++) {
            const float4 st = lds128(rs + wv * 88 * 16);
            sq += bb ? st.y : st.x; sm += st.z;
        }
#pragma unroll
        for (int wv = 0; wv < 8; wv++) {
            const float4 u = lds128(ra + wv * 88 * 16);
            v0 += u.x; v1 += u.y; cs += u.z;
        }
        const float ov = __shfl_xor_sync(0xffffffffu, bb ? v0 : v1, 1), ocs = __shfl_xor_sync(0xffffffffu, cs, 1);
        const float mean = sm * (1.f / D_MODEL);
        const float var = fmaxf(fmaf(-mean, mean, sq * (1.f / D_MODEL)), 0.f);
        const float mb = bfr(mean);
        float sd;
        asm("sqrt.approx.ftz.f32 %0, %1;" : "=f"(sd) : "f"(bfr(bfr(var) + 1e-5f)));
        const float isd = rcp(bfr(sd));
        const float gt = bfr(fmaf(-mb, bb ? ocs : cs, bb ? ov : v0) * isd);
        const float up = bfr(fmaf(-mb, bb ? cs : ocs, bb ? v1 : ov) * isd);
        const float act = bfr(gt * rcp(1.f + ex2(-gt * LOG2E))) * up;
        if (at < 80) asm volatile("st.shared.u16 [%0], %1;" ::"r"(wa), "h"((unsigned short)pack_bf16(act, 0.f)) : "memory");
        TLM(12);
        bar_arrive(BAR_ACT, 352);
        return;
    }

    const int g = lane >> 2, t4 = lane & 3;
    unsigned tag;
    {
        const uint32_t* xp = reinterpret_cast<const uint32_t*>(x + (warp >> 2) * D_MODEL);
        uint32_t xu[9], xo[3];
#pragma unroll
        for (int i = 0; i < 9; i++) xu[i] = __ldg(xp + lane + 32 * i);
        tag = ld_relaxed32(&g_sync[0]) + 1;
        const int wq4 = warp & 3;
        xo[0] = wq4 == 0 ? xu[0] : wq4 == 1 ? xu[1] : wq4 == 2 ? xu[2] : xu[3];
        xo[1] = wq4 == 0 ? xu[4] : wq4 == 1 ? xu[5] : wq4 == 2 ? xu[6] : xu[7];
        xo[2] = xu[8];
        float s = 0.f;
#pragma unroll
        for (int i = 0; i < 9; i++) s += bf_lo(xu[i]) + bf_hi(xu[i]);
#pragma unroll
        for (int o = 16; o; o >>= 1) s += __shfl_xor_sync(0xffffffffu, s, o);
        const float mean = __fdiv_rn(s, (float)D_MODEL);
        float q2 = 0.f;
#pragma unroll
        for (int i = 0; i < 9; i++) {
            const float d0 = bf_lo(xu[i]) - mean, d1 = bf_hi(xu[i]) - mean;
            q2 = fmaf(d0, d0, fmaf(d1, d1, q2));
        }
#pragma unroll
        for (int o = 16; o; o >>= 1) q2 += __shfl_xor_sync(0xffffffffu, q2, o);
        const float mb = bfr(mean);
        const float sd = bfr(__fsqrt_rn(bfr(bfr(__fdiv_rn(q2, (float)D_MODEL)) + 1e-5f)));
#pragma unroll 1
        for (int i = 0; i < 3; i++) {
            const uint32_t u = i == 0 ? xo[0] : i == 1 ? xo[1] : xo[2];
            const int wi = i < 2 ? 4 * i + wq4 : 8;
            *reinterpret_cast<uint32_t*>(smem + SM_XN + (warp >> 2) * XN_PITCH + 4 * (lane + 32 * wi)) =
                pack_bf16(__fdiv_rn(bfr(bf_lo(u) - mb), sd), __fdiv_rn(bfr(bf_hi(u) - mb), sd));
        }
        bar_sync(0, 320);
        uint32_t xb[12];
        const uint32_t xa = sb + SM_XN + (lane & 1) * XN_PITCH + (warp * 72 + 8 * (lane >> 3)) * 2;
        ldsm4(*reinterpret_cast<uint32_t(*)[4]>(&xb[0]), xa);
        ldsm4(*reinterpret_cast<uint32_t(*)[4]>(&xb[4]), xa + 64);
        ldsm1(xb[8], xa + 128);
        mbar_wait(bar_w + 8 * (warp >> 1), 0);
        const uint32_t wa = sb + SM_W1 + (warp * 72 + (lane & 7) + 8 * (lane >> 4)) * 64;
        float qa[2][4];
#pragma unroll
        for (int j = 0; j < 2; j++) {
            const uint32_t ad = wa + (((2 * j + ((lane >> 3) & 1)) ^ ((lane >> 1) & 3)) << 4);
            qa[j][0] = qa[j][1] = qa[j][2] = qa[j][3] = 0.f;
#pragma unroll
            for (int ks = 0; ks < 4; ks++) {
                uint32_t a4[4];
                ldsm4t(a4, ad + ks * 16 * 64);
                mma16816(qa[j], a4[0], a4[1], a4[2], a4[3], xb[2 * ks], xb[2 * ks + 1]);
            }
            uint32_t a0, a1;
            ldsm2t(a0, a1, ad + 64 * 64);
            mma1688(qa[j], a0, a1, xb[8]);
        }
#pragma unroll
        for (int j = 0; j < 2; j++) {
            const float lo = (t4 & 1) ? qa[j][1] : qa[j][0], hi = (t4 & 1) ? qa[j][3] : qa[j][2];
            red[warp * 64 + (t4 & 1) * 32 + 16 * j + g + 8 * (t4 >> 1)] = (t4 & 2) ? hi : lo;
        }
        bar_sync(BAR_ALL, 256);
        if (warp == 0) {
            float s0 = 0.f, s1 = 0.f;
#pragma unroll
            for (int wv = 0; wv < 8; wv++) {
                const float2 v = *reinterpret_cast<const float2*>(red + wv * 64 + lane * 2);
                s0 += v.x; s1 += v.y;
            }
            st_relaxed64(&g_pq[lane >> 4][hkv][r * 16 + (lane & 15)], pack_bf16(s0, s1), tag);
            if (lane == 0) TL(3);
        }
    }

    if (warp < 4) {
        float* const ml = reinterpret_cast<float*>(smem + SM_ML);
        uint32_t* const qs = reinterpret_cast<uint32_t*>(smem + SM_Q);
        {
            uint2 v0, v1;
            unsigned n = 0;
            while (true) {
                __nanosleep(Q_SLEEP);
                v0 = ld_relaxed64(&g_pq[0][hkv][tid]);
                v1 = ld_relaxed64(&g_pq[1][hkv][tid]);
                if (v0.y == tag && v1.y == tag) break;
                if (++n > SPIN_LIMIT) __trap();
            }
            qs[tid] = v0.x; qs[128 + tid] = v1.x;
            bar_sync(BAR_MAIN, 128);
        }
        if (tid == 0) TL(4);
        uint32_t koff[4], voff[4];
        {
            const int l7 = lane & 7;
            const uint32_t kb = (warp * 16 + l7 + 8 * ((lane >> 3) & 1)) * 128;
            const uint32_t vb = (warp * 16 + l7 + 8 * (lane >> 4)) * 128;
#pragma unroll
            for (int i = 0; i < 4; i++) {
                koff[i] = sb + SM_RING + kb + (((2 * i + (lane >> 4)) ^ l7) << 4);
                voff[i] = sb + SM_RING + SLOT_BYTES + vb + (((2 * i + ((lane >> 3) & 1)) ^ l7) << 4);
            }
        }
        uint32_t dst1 = 0;
#pragma unroll 1
        for (int b = 0; b < 2; b++) {
            uint32_t qb[8][2];
#pragma unroll
            for (int ks = 0; ks < 8; ks++) {
                qb[ks][0] = qs[b * 128 + (g & 1) * 64 + ks * 8 + t4];
                qb[ks][1] = qs[b * 128 + (g & 1) * 64 + ks * 8 + 4 + t4];
            }
            float o[8][4];
#pragma unroll
            for (int i = 0; i < 8; i++) { o[i][0] = o[i][1] = o[i][2] = o[i][3] = 0.f; }
            float m0 = -INFINITY, m1 = -INFINITY, mL0 = -INFINITY, mL1 = -INFINITY, l0 = 0.f, l1 = 0.f;
#pragma unroll 1
            for (int t = 0; t < NTILES / 2; t++) {
                const int slot = (2 * t) & (NSLOTS - 1);
                const uint32_t ph = (t >> 2) & 1;
                const uint32_t so = slot * SLOT_BYTES;
                mbar_wait(bar_full + 8 * slot, ph);
                uint32_t a[8][4];
#pragma unroll
                for (int ks = 0; ks < 8; ks++) ldsm4(a[ks], koff[ks & 3] + so + (ks >> 2) * 8192);
                __syncwarp();
                if (lane == 0) mbar_arrive(bar_empty + 8 * slot);
                float c[4] = {0.f, 0.f, 0.f, 0.f}, c2[4] = {0.f, 0.f, 0.f, 0.f};
#pragma unroll
                for (int ks = 0; ks < 8; ks += 2) {
                    mma16816(c, a[ks][0], a[ks][1], a[ks][2], a[ks][3], qb[ks][0], qb[ks][1]);
                    mma16816(c2, a[ks + 1][0], a[ks + 1][1], a[ks + 1][2], a[ks + 1][3], qb[ks + 1][0], qb[ks + 1][1]);
                }
                uint32_t u0 = pack_bf16(c[0] + c2[0], c[1] + c2[1]), u1 = pack_bf16(c[2] + c2[2], c[3] + c2[3]);
                u0 = pack_bf16(bf_lo(u0) * SCALE, bf_hi(u0) * SCALE);
                u1 = pack_bf16(bf_lo(u1) * SCALE, bf_hi(u1) * SCALE);
                const float s0 = bf_lo(u0), s1 = bf_hi(u0), s2 = bf_lo(u1), s3 = bf_hi(u1);
                float x0 = fmaxf(s0, s2), x1 = fmaxf(s1, s3);
                if (__any_sync(0xffffffffu, x0 > m0 || x1 > m1)) {
#pragma unroll
                    for (int of = 4; of < 32; of <<= 1) {
                        x0 = fmaxf(x0, __shfl_xor_sync(0xffffffffu, x0, of));
                        x1 = fmaxf(x1, __shfl_xor_sync(0xffffffffu, x1, of));
                    }
                    m0 = fmaxf(m0, x0); m1 = fmaxf(m1, x1);
                    const float n0 = m0 * LOG2E, n1 = m1 * LOG2E;
                    const float al0 = ex2(mL0 - n0), al1 = ex2(mL1 - n1);
                    mL0 = n0; mL1 = n1;
                    l0 *= al0; l1 *= al1;
#pragma unroll
                    for (int i = 0; i < 8; i++) { o[i][0] *= al0; o[i][1] *= al1; o[i][2] *= al0; o[i][3] *= al1; }
                }
                const float p0 = ex2(fmaf(s0, LOG2E, -mL0)), p1 = ex2(fmaf(s1, LOG2E, -mL1));
                const float p2 = ex2(fmaf(s2, LOG2E, -mL0)), p3 = ex2(fmaf(s3, LOG2E, -mL1));
                l0 += p0 + p2; l1 += p1 + p3;
                const uint32_t pb0 = movm(pack_bf16(p0, p1)), pb1 = movm(pack_bf16(p2, p3));
                mbar_wait(bar_full + 8 * slot + 8, ph);
#pragma unroll
                for (int mt = 0; mt < 8; mt++) ldsm4t(a[mt], voff[mt & 3] + so + (mt >> 2) * 8192);
                __syncwarp();
                if (lane == 0) mbar_arrive(bar_empty + 8 * slot + 8);
#pragma unroll
                for (int mt = 0; mt < 8; mt++) mma16816(o[mt], a[mt][0], a[mt][1], a[mt][2], a[mt][3], pb0, pb1);
            }
            TLM(5);
#pragma unroll
            for (int of = 4; of < 32; of <<= 1) {
                l0 += __shfl_xor_sync(0xffffffffu, l0, of);
                l1 += __shfl_xor_sync(0xffffffffu, l1, of);
            }
            if (lane < 2) *reinterpret_cast<float2*>(ml + lane * 8 + warp * 2) = lane ? make_float2(mL1, l1) : make_float2(mL0, l0);
            {
                float* dst = red + warp * 288 + (t4 & 1) * 144 + g + 8 * (t4 >> 1);
#pragma unroll
                for (int mt = 0; mt < 8; mt++) {
                    const float lo = (t4 & 1) ? o[mt][1] : o[mt][0], hi = (t4 & 1) ? o[mt][3] : o[mt][2];
                    dst[16 * mt] = (t4 & 2) ? hi : lo;
                }
            }
            if (b == 0) {
                bar_sync(BAR_RDY, 256);
                const int rd = GRP_MAP ? (tid >> 4) * 16 + hkv : hkv * 8 + (tid >> 4);
                dst1 = near_of(X_P1 + (rd >> 1) * 8192, smem[SM_HOME + rd]) + (rd & 1) * 2048 + r * 256 + (tid & 15) * 16;
            } else {
                bar_sync(BAR_MAIN, 128);
                if (P1_HINT) bar_arrive(BAR_RDY, 256);
            }
            dst1 ^= 4096;
            {
                const int h = tid >> 6, j = tid & 63;
                const float4 w01 = *reinterpret_cast<const float4*>(ml + h * 8), w23 = *reinterpret_cast<const float4*>(ml + h * 8 + 4);
                const float* op = red + h * 144 + 2 * j;
                const float2 v0 = *reinterpret_cast<const float2*>(op), v1 = *reinterpret_cast<const float2*>(op + 288);
                const float2 v2 = *reinterpret_cast<const float2*>(op + 576), v3 = *reinterpret_cast<const float2*>(op + 864);
                const float M = fmaxf(fmaxf(w01.x, w01.z), fmaxf(w23.x, w23.z));
                const float e0 = ex2(w01.x - M), e1 = ex2(w01.z - M), e2 = ex2(w23.x - M), e3 = ex2(w23.z - M);
                const float L = fmaf(e0, w01.y, e1 * w01.w) + fmaf(e2, w23.y, e3 * w23.w);
                const float o0 = fmaf(e0, v0.x, e1 * v1.x) + fmaf(e2, v2.x, e3 * v3.x);
                const float o1 = fmaf(e0, v0.y, e1 * v1.y) + fmaf(e2, v2.y, e3 * v3.y);
                const float inv = rcp(L);
                st_relaxed128(g_x + dst1, __float_as_uint(o0 * inv), __float_as_uint(o1 * inv), __float_as_uint(M + lg2(L)), tag);
            }
            TLM(6);
        }
    } else {
        const int hw = warp - 4, ht = tid - 128;
        bar_sync(BAR_PROBE, 224);
        const unsigned side = (smem[SM_HOME + 128] + smem[SM_HOME + 129] + smem[SM_HOME + 130]) >> 1;
        if (CLEAR_AT) { while (prog[0] < CLEAR_AT) __nanosleep(1000); }
        if (cta < NRED) {
#pragma unroll 1
            for (int i = 0; i < 6; i++) {
                const uint32_t off = i < 4 ? X_P2 + cta * 8192 + i * 2048 : near_of(X_P4 + cta * 8192, side) + (i & 1) * 2048;
                st_relaxed128(g_x + off + ht * 16, SENTINEL, SENTINEL, SENTINEL, SENTINEL);
            }
        } else if (cta < NRED + 16) {
            unsigned char* p = g_x + X_P3 + (cta - NRED) * 4096 + ht * 16;
            st_relaxed128(p, SENTINEL, SENTINEL, SENTINEL, SENTINEL);
            if (ht < 16) st_relaxed128(p + 2048, SENTINEL, SENTINEL, SENTINEL, SENTINEL);
        }
        if (ht == 0) st_relaxed32(&g_home[cta], side | (DBG_TIMELINE ? *reinterpret_cast<unsigned*>(smem + SM_HOME + 128) << 8 : 0));
        __threadfence();
        bar_sync(BAR_HELP, 128);
        if (ht == 0) {
            red_add(&g_sync[32]);
            unsigned n = 0;
            while (ld_relaxed32(&g_sync[32]) < NCTA) {
                if (++n > SPIN_LIMIT) __trap();
                __nanosleep(500);
            }
            __threadfence();
        }
        bar_sync(BAR_HELP, 128);
        smem[SM_HOME + ht] = (unsigned char)ld_relaxed32(&g_home[ht]);
        bar_sync(BAR_HELP, 128);
        if (ht == 0) TL(25);
        bar_arrive(BAR_RDY, 256);
        uint32_t wb[9][2][4];
#pragma unroll 1
        for (int p = 4; p < 8; p++) mbar_wait(bar_w + 8 * p, 0);
#pragma unroll
        for (int j = 0; j < 9; j++) {
            const int nt = hw * 18 + 2 * j + ((lane >> 3) & 1);
            const uint32_t ad = sb + SM_WO + (lane >> 4) * ROW8_PIECE + (nt >> 3) * 1024 + (lane & 7) * 128 + (((nt ^ lane) & 7) << 4);
            ldsm4t(wb[j][0], ad);
            ldsm4t(wb[j][1], ad + 2 * ROW8_PIECE);
        }
        uint32_t dst2[5];
#pragma unroll
        for (int i = 0; i < 5; i++) {
            const int rd = min(hw * 18 + 4 * i + t4, NRED - 1);
            dst2[i] = near_of(X_P2 + rd * 8192, smem[SM_HOME + rd]) + cta * 32 + g * 4;
        }
        uint32_t src1 = near_of(X_P1 + (cta >> 1) * 8192, side) + (cta & 1) * 2048 + ht * 16;
        uint32_t src2 = near_of(X_P2 + cta * 8192, side) + ht * 16;
#pragma unroll 1
        for (int b = 0; b < 2; b++) {
            src1 ^= 4096; src2 ^= 4096;
#pragma unroll
            for (int i = 0; i < 5; i++) { dst2[i] ^= 4096; PIN(dst2[i]); }
            uint32_t xres = 0, dst3 = X_P3 + (lane >> 2) * 8192 + cta * 32 + b * 16 + t4 * 4;
            if (cta < NRED) xres = __ldg(reinterpret_cast<const uint32_t*>(x + b * D_MODEL + cta * 8) + t4);
            PIN(xres); PIN(dst3); PIN(src1); PIN(src2);
            unsigned n = 0;
            while (prog[0] < (b ? NKV : NTILES + B0_LAG)) {
                if (++n > SPIN_LIMIT) __trap();
                __nanosleep(HELP_SLEEP);
            }
            uint4 u = ld_relaxed128(g_x + src1);
            if (P1_HINT && b) bar_sync(BAR_RDY, 256);
            while (u.w != tag) {
                if (++n > SPIN_LIMIT) __trap();
                if (b == 0) __nanosleep(256);
                u = ld_relaxed128(g_x + src1);
            }
            uint4* px = reinterpret_cast<uint4*>(smem + SM_PX);
            px[ht] = u;
            bar_sync(BAR_HELP, 128);
            if (tid == 128) TL(7);
            uint32_t ob;
            {
                uint4 v[4];
#pragma unroll
                for (int i = 0; i < 4; i++) v[i] = px[i * 32 + lane];
                float W = fmaxf(fmaxf(__uint_as_float(v[0].z), __uint_as_float(v[1].z)), fmaxf(__uint_as_float(v[2].z), __uint_as_float(v[3].z)));
                W = fmaxf(W, __shfl_xor_sync(0xffffffffu, W, 16));
                float e[4];
#pragma unroll
                for (int i = 0; i < 4; i++) e[i] = ex2(__uint_as_float(v[i].z) - W);
                float den = (e[0] + e[1]) + (e[2] + e[3]);
                float o0 = fmaf(e[0], __uint_as_float(v[0].x), e[1] * __uint_as_float(v[1].x)) + fmaf(e[2], __uint_as_float(v[2].x), e[3] * __uint_as_float(v[3].x));
                float o1 = fmaf(e[0], __uint_as_float(v[0].y), e[1] * __uint_as_float(v[1].y)) + fmaf(e[2], __uint_as_float(v[2].y), e[3] * __uint_as_float(v[3].y));
                den += __shfl_xor_sync(0xffffffffu, den, 16);
                o0 += __shfl_xor_sync(0xffffffffu, o0, 16);
                o1 += __shfl_xor_sync(0xffffffffu, o1, 16);
                const float inv = rcp(den);
                ob = pack_bf16(o0 * inv, o1 * inv);
            }
            uint32_t oa[4];
#pragma unroll
            for (int i = 0; i < 4; i++) oa[i] = __shfl_sync(0xffffffffu, ob, 4 * i + t4);
            float y[9][4];
#pragma unroll
            for (int j = 0; j < 9; j++) {
                y[j][0] = y[j][1] = y[j][2] = y[j][3] = 0.f;
                mma16816(y[j], wb[j][0][0], wb[j][0][1], wb[j][0][2], wb[j][0][3], oa[0], oa[1]);
            }
#pragma unroll
            for (int j = 0; j < 9; j++) mma16816(y[j], wb[j][1][0], wb[j][1][1], wb[j][1][2], wb[j][1][3], oa[2], oa[3]);
#pragma unroll
            for (int i = 0; i < 5; i++) {
                const float lo = (t4 & 1) ? y[2 * i][2] : y[2 * i][0];
                const float hi = i < 4 ? ((t4 & 1) ? y[(2 * i + 1) % 9][2] : y[(2 * i + 1) % 9][0]) : lo;
                if (i < 4 || t4 < 2) st_relaxed32(g_x + dst2[i], __float_as_uint((t4 & 2) ? hi : lo));
            }
            TLM(8);
            if (cta < NRED) {
                while (prog[0] < NTILES + 2 * B0_LAG) __nanosleep(HELP_SLEEP);
                uint4 v0 = ld_relaxed128(g_x + src2), v1 = ld_relaxed128(g_x + src2 + 2048);
                while (!(valid4(v0) && valid4(v1))) {
                    if (++n > SPIN_LIMIT) __trap();
                    if (b == 0) __nanosleep(256);
                    if (!valid4(v0)) v0 = ld_relaxed128(g_x + src2);
                    if (!valid4(v1)) v1 = ld_relaxed128(g_x + src2 + 2048);
                }
                __syncwarp();
                TLM(21);
                const float s0 = __uint_as_float(v0.x) + __uint_as_float(v1.x), s1 = __uint_as_float(v0.y) + __uint_as_float(v1.y);
                const float s2 = __uint_as_float(v0.z) + __uint_as_float(v1.z), s3 = __uint_as_float(v0.w) + __uint_as_float(v1.w);
                const bool k1 = lane & 2, k2 = lane & 4;
                const float a0 = (k1 ? s2 : s0) + __shfl_xor_sync(0xffffffffu, k1 ? s0 : s2, 2);
                const float a1 = (k1 ? s3 : s1) + __shfl_xor_sync(0xffffffffu, k1 ? s1 : s3, 2);
                float a = (k2 ? a1 : a0) + __shfl_xor_sync(0xffffffffu, k2 ? a0 : a1, 4);
                a += __shfl_xor_sync(0xffffffffu, a, 8);
                a += __shfl_xor_sync(0xffffffffu, a, 16);
                float* red2 = reinterpret_cast<float*>(smem + SM_RED2);
                if (lane < 8) red2[hw * 8 + (lane & 1) * 4 + (lane & 2) + (lane >> 2)] = a;
                bar_sync(BAR_HELP, 128);
                if (hw == 0) {
                    const float2 c0 = *reinterpret_cast<const float2*>(red2 + 2 * t4), c1 = *reinterpret_cast<const float2*>(red2 + 8 + 2 * t4);
                    const float2 c2 = *reinterpret_cast<const float2*>(red2 + 16 + 2 * t4), c3 = *reinterpret_cast<const float2*>(red2 + 24 + 2 * t4);
                    const uint32_t at = pack_bf16((c0.x + c1.x) + (c2.x + c3.x), (c0.y + c1.y) + (c2.y + c3.y));
                    const uint32_t hp = pack_bf16(bf_lo(xres) + bf_lo(at), bf_hi(xres) + bf_hi(at));
                    st_relaxed32(g_x + dst3, hp);
                    st_relaxed32(g_x + dst3 + 4096, hp);
                    if (lane < 4) *reinterpret_cast<uint32_t*>(smem + SM_HRES + b * 16 + lane * 4) = hp;
                    if (lane == 0) TL(9);
                }
            }
        }
    }

    uint32_t fa[5][18];
    {
        const uint32_t w1a = sb + SM_W1 + (warp * 72 + (lane & 7) + 8 * (lane >> 4)) * 80 + ((lane >> 3) & 1) * 16;
        const uint32_t w3r = sb + SM_RING + (warp >> 1) * SLOT_BYTES + ((warp & 1) * 72 + (lane & 7) + 8 * (lane >> 4)) * 80;
        const uint32_t w3a = w3r + ((lane >> 3) & 1) * 16;
        const uint32_t wma = ((lane >> 3) & 1) ? w3r + 64 : w1a + 64;
        mbar_wait(bar_l + 8 * (warp >> 1), 0);
#pragma unroll
        for (int j = 0; j < 5; j++) {
            if (j == 2) mbar_wait(bar_l + 8 * (4 + (warp >> 1)), 0);
            const uint32_t base = j < 2 ? w1a + j * 32 : j < 4 ? w3a + (j - 2) * 32 : wma;
#pragma unroll
            for (int ks = 0; ks < 4; ks++) ldsm4t(*reinterpret_cast<uint32_t(*)[4]>(&fa[j][ks * 4]), base + ks * 16 * 80);
            ldsm2t(fa[j][16], fa[j][17], base + 64 * 80);
        }
    }
    uint32_t dst4[3], w2a[5], w2c[3];
#pragma unroll
    for (int i = 0; i < 3; i++) {
        const int rd = min(warp * 9 + 4 * i + (g >> 1), NRED - 1);
        dst4[i] = near_of(X_P4 + rd * 8192, smem[SM_HOME + rd]) + cta * 32 + (lane & 7) * 4;
        PIN(dst4[i]);
        const int nt = min(warp * 9 + 4 * i + (lane >> 3), 71);
        w2c[i] = sb + SM_W2 + (lane & 7) * 128 + (nt >> 3) * 1024 + (((nt ^ lane) & 7) << 4);
        PIN(w2c[i]);
    }
#pragma unroll
    for (int i = 0; i < 5; i++) {
        const int nt = min(warp * 9 + 2 * i + (lane >> 4), 71);
        w2a[i] = sb + SM_W2 + (1 + ((lane >> 3) & 1)) * ROW8_PIECE + (lane & 7) * 128 + (nt >> 3) * 1024 + (((nt ^ lane) & 7) << 4);
        PIN(w2a[i]);
    }
    uint32_t src4 = near_of(X_P4 + cta * 8192, smem[SM_HOME + cta]) + tid * 16;
    PIN(src4);
    TLM(10);
    {
        const bool data = (lane & 7) < 2;
        uint32_t ha = data ? sb + SM_HS + (warp * 18 + (lane >> 3) * 2 + (lane & 1)) * 16 : sb + SM_ONES;
        uint32_t hs = data ? 128 : 0;
        uint32_t rd1 = sb + SM_RED + (warp * 88 + 2 * g) * 16 + 8 * t4;
        PIN(ha); PIN(hs); PIN(rd1);
        if (lane < 18) {
            const unsigned char* hp = g_x + near_of(X_P3 + (cta & 7) * 8192, smem[SM_HOME + cta]) + (warp * 18 + lane) * 16;
            unsigned n = 0;
            uint4 u = ld_relaxed128(hp);
            while (!valid4(u)) {
                if (++n > SPIN_LIMIT) __trap();
                u = ld_relaxed128(hp);
            }
            *reinterpret_cast<uint4*>(smem + SM_HS + (warp * 18 + lane) * 16) = u;
        }
        __syncwarp();
        TLM(11);
        uint32_t hb[12];
        ldsm4(*reinterpret_cast<uint32_t(*)[4]>(&hb[0]), ha);
        ldsm4(*reinterpret_cast<uint32_t(*)[4]>(&hb[4]), ha + hs);
        ldsm1(hb[8], ha + 2 * hs);
        float gu[6][4];
#pragma unroll
        for (int j = 0; j < 6; j++) { gu[j][0] = gu[j][1] = gu[j][2] = gu[j][3] = 0.f; }
#pragma unroll
        for (int ks = 0; ks < 4; ks++) {
#pragma unroll
            for (int j = 0; j < 5; j++)
                mma16816(gu[j], fa[j][ks * 4], fa[j][ks * 4 + 1], fa[j][ks * 4 + 2], fa[j][ks * 4 + 3], hb[2 * ks], hb[2 * ks + 1]);
            mma16816(gu[5], hb[2 * ks], hb[2 * ks], hb[2 * ks + 1], hb[2 * ks + 1], hb[2 * ks], hb[2 * ks + 1]);
        }
#pragma unroll
        for (int j = 0; j < 5; j++) mma1688(gu[j], fa[j][16], fa[j][17], hb[8]);
        mma1688(gu[5], hb[8], hb[8], hb[8]);
        if (t4 < 2) {
#pragma unroll
            for (int j = 0; j < 4; j++) {
                sts64(rd1 + ((j & 1) * 32 + (j >> 1)) * 16, gu[j][0], gu[j][1]);
                sts64(rd1 + ((j & 1) * 32 + 16 + (j >> 1)) * 16, gu[j][2], gu[j][3]);
            }
            sts64(rd1 + 64 * 16, gu[4][0], gu[4][1]);
            sts64(rd1 + 65 * 16, gu[4][2], gu[4][3]);
            sts64(rd1 + (80 - g) * 16, gu[5][0], gu[5][1]);
        }
    }
    TLM(23);
    bar_arrive(BAR_F1, 352);
    {
        uint32_t wc[12], wp[5][4], wq[5][4];
        mbar_wait(bar_l + 8 * 8, 0);
#pragma unroll
        for (int i = 0; i < 3; i++) ldsm4t(*reinterpret_cast<uint32_t(*)[4]>(&wc[4 * i]), w2c[i]);
        mbar_wait(bar_l + 8 * 9, 0);
        mbar_wait(bar_l + 8 * 10, 0);
#pragma unroll
        for (int i = 0; i < 5; i++) ldsm4t(wp[i], w2a[i]);
        uint32_t aa0 = sb + SM_ACT + (lane & 1) * 80 + (lane >> 3) * 16;
        PIN(aa0);
        bar_sync(BAR_ACT, 352);
        uint32_t aa[4], a8;
        ldsm4(aa, aa0 + 16);
        ldsm1(a8, aa0);
        float z[9][4];
#pragma unroll
        for (int j = 0; j < 9; j++) {
            z[j][0] = z[j][1] = z[j][2] = z[j][3] = 0.f;
            mma16816v(z[j], aa[0], aa[0], aa[1], aa[1], wp[j >> 1][(j & 1) * 2], wp[j >> 1][(j & 1) * 2 + 1]);
        }
        mbar_wait(bar_l + 8 * 11, 0);
        mbar_wait(bar_l + 8 * 12, 0);
#pragma unroll
        for (int i = 0; i < 5; i++) ldsm4t(wq[i], w2a[i] + 2 * ROW8_PIECE);
        TLM(16);
        if (!(cta & 1)) {
#pragma unroll
            for (int j = 0; j < 9; j++) mma1688(z[j], a8, a8, wc[j]);
        }
#pragma unroll
        for (int j = 0; j < 9; j++) mma16816(z[j], aa[2], aa[2], aa[3], aa[3], wq[j >> 1][(j & 1) * 2], wq[j >> 1][(j & 1) * 2 + 1]);
        uint32_t zp[9];
#pragma unroll
        for (int j = 0; j < 9; j++) zp[j] = pack_bf16(z[j][0], z[j][1]);
        const bool q1 = lane & 8, q2 = lane & 16;
        st_relaxed32(g_x + dst4[0], q2 ? (q1 ? zp[3] : zp[2]) : (q1 ? zp[1] : zp[0]));
        st_relaxed32(g_x + dst4[1], q2 ? (q1 ? zp[7] : zp[6]) : (q1 ? zp[5] : zp[4]));
        if (lane < 8) st_relaxed32(g_x + dst4[2], zp[8]);
    }
    TLM(13);
    if (cta < NRED) {
        if (P4_DELAY) { const long long t0 = clock64(); while (clock64() - t0 < P4_DELAY) {} }
        uint4 v = ld_relaxed128(g_x + src4);
        __nv_bfloat16* op = out + ((tid >> 3) & 1) * D_MODEL + cta * 8 + (tid & 7);
        const float hres = __bfloat162float(reinterpret_cast<const __nv_bfloat16*>(smem + SM_HRES)[tid & 15]);
        unsigned n = 0;
        while (!valid4(v)) {
            if (++n > SPIN_LIMIT) __trap();
            v = ld_relaxed128(g_x + src4);
        }
        __syncwarp();
        TLM(22);
        const bool k1 = lane & 2, k2 = lane & 4, k3 = lane & 8;
        const uint32_t u0 = k1 ? v.z : v.x, u1 = k1 ? v.w : v.y;
        const uint32_t w0 = __shfl_xor_sync(0xffffffffu, k1 ? v.x : v.z, 2), w1 = __shfl_xor_sync(0xffffffffu, k1 ? v.y : v.w, 2);
        const float s0 = bf_lo(u0) + bf_lo(w0), s1 = bf_hi(u0) + bf_hi(w0), s2 = bf_lo(u1) + bf_lo(w1), s3 = bf_hi(u1) + bf_hi(w1);
        const float a0 = (k2 ? s2 : s0) + __shfl_xor_sync(0xffffffffu, k2 ? s0 : s2, 4);
        const float a1 = (k2 ? s3 : s1) + __shfl_xor_sync(0xffffffffu, k2 ? s1 : s3, 4);
        float a = (k3 ? a1 : a0) + __shfl_xor_sync(0xffffffffu, k3 ? a0 : a1, 8);
        a += __shfl_xor_sync(0xffffffffu, a, 16);
        float* red4 = reinterpret_cast<float*>(smem + SM_RED4);
        if (lane < 16) red4[warp * 16 + (lane & 1) * 8 + (lane & 2) * 2 + ((lane >> 1) & 2) + (lane >> 3)] = a;
        bar_sync(BAR_ALL, 256);
        if (tid < 16) {
            const float tot = ((red4[tid] + red4[16 + tid]) + (red4[32 + tid] + red4[48 + tid])) +
                              ((red4[64 + tid] + red4[80 + tid]) + (red4[96 + tid] + red4[112 + tid]));
            *op = __float2bfloat16_rn(hres + bfr(tot));
            if (cta == 0 && tid == 0) {
                st_relaxed32(&g_sync[0], tag);
                st_relaxed32(&g_sync[32], 0);
                st_relaxed32(&g_sync[64], 0);
            }
        }
        if (tid == 0) TL(14);
    }
}

typedef CUresult (*EncodeTiledFn)(CUtensorMap*, CUtensorMapDataType, cuuint32_t, void*, const cuuint64_t*, const cuuint64_t*,
                                  const cuuint32_t*, const cuuint32_t*, CUtensorMapInterleave, CUtensorMapSwizzle,
                                  CUtensorMapL2promotion, CUtensorMapFloatOOBfill);

static void encode2d(EncodeTiledFn enc, CUtensorMap* m, void* p, uint64_t cols, uint64_t rows, uint32_t bc, uint32_t br,
                     CUtensorMapSwizzle swz = CU_TENSOR_MAP_SWIZZLE_NONE) {
    cuuint64_t gd[2] = {cols, rows};
    cuuint64_t gs[1] = {cols * 2};
    cuuint32_t bx[2] = {bc, br};
    cuuint32_t es[2] = {1, 1};
    enc(m, CU_TENSOR_MAP_DATA_TYPE_BFLOAT16, 2, p, gd, gs, bx, es, CU_TENSOR_MAP_INTERLEAVE_NONE, swz,
        W_PROMO, CU_TENSOR_MAP_FLOAT_OOB_FILL_NONE);
}
static void encode_rows(EncodeTiledFn enc, CUtensorMap* m, void* p, uint64_t rows) {
    cuuint64_t gd[3] = {64, rows, 9};
    cuuint64_t gs[2] = {D_MODEL * 2, 128};
    cuuint32_t bx[3] = {64, 8, 9};
    cuuint32_t es[3] = {1, 1, 1};
    enc(m, CU_TENSOR_MAP_DATA_TYPE_BFLOAT16, 3, p, gd, gs, bx, es, CU_TENSOR_MAP_INTERLEAVE_NONE, CU_TENSOR_MAP_SWIZZLE_128B,
        CU_TENSOR_MAP_L2_PROMOTION_NONE, CU_TENSOR_MAP_FLOAT_OOB_FILL_NONE);
}
static void encode_kv(EncodeTiledFn enc, CUtensorMap* m, void* p) {
    cuuint64_t gd[3] = {64, (cuuint64_t)2 * HKV * SK, 2};
    cuuint64_t gs[2] = {256, 128};
    cuuint32_t bx[3] = {64, TILE_KEYS, 2};
    cuuint32_t es[3] = {1, 1, 1};
    enc(m, CU_TENSOR_MAP_DATA_TYPE_BFLOAT16, 3, p, gd, gs, bx, es, CU_TENSOR_MAP_INTERLEAVE_NONE, CU_TENSOR_MAP_SWIZZLE_128B,
        CU_TENSOR_MAP_L2_PROMOTION_NONE, CU_TENSOR_MAP_FLOAT_OOB_FILL_NONE);
}

extern "C" void kernel_launch(void* const* d_in, const int* in_sizes, int n_in, void* d_out, int out_size) {
    (void)in_sizes; (void)n_in; (void)out_size;
    static EncodeTiledFn enc = nullptr;
    if (!enc) {
        cudaDriverEntryPointQueryResult qr;
        cudaGetDriverEntryPoint("cuTensorMapEncodeTiled", (void**)&enc, cudaEnableDefault, &qr);
        cudaFuncSetAttribute(fused_decode_kernel, cudaFuncAttributeMaxDynamicSharedMemorySize, SM_TOTAL);
    }
    CUtensorMap mk, mv, mwo, mw1, mw3, mw2, mwq;
    encode2d(enc, &mwq, d_in[3], QDIM, D_MODEL, 32, 144, CU_TENSOR_MAP_SWIZZLE_64B);
    encode_kv(enc, &mk, d_in[1]);
    encode_kv(enc, &mv, d_in[2]);
    encode_rows(enc, &mwo, d_in[4], QDIM);
    encode2d(enc, &mw1, d_in[6], FF, D_MODEL, 40, 144);
    encode2d(enc, &mw3, d_in[7], FF, D_MODEL, 40, 144);
    encode_rows(enc, &mw2, d_in[8], FF);
    fused_decode_kernel<<<NCTA, NTHREADS, SM_TOTAL>>>(mk, mv, mwo, mw1, mw3, mw2, mwq, (const __nv_bfloat16*)d_in[0],
                                                     (__nv_bfloat16*)d_out);
}
```

```cpp
#include <cuda_runtime.h>
#include <cuda_bf16.h>
#include <cuda.h>
#include <stdint.h>

#define DBG_TIMELINE 0

namespace {

constexpr int D_MODEL = 576;
constexpr int HKV = 16;
constexpr int SK = 32768;
constexpr int QDIM = 4096;
constexpr int FF = 4608;

constexpr int NCTA = 128;
constexpr int NTHREADS = 384;
constexpr int TILE_KEYS = 64;
constexpr int NTILES = SK / 4 / TILE_KEYS;
constexpr int SLOT_BYTES = TILE_KEYS * 256;
constexpr int NSLOTS = 8;
constexpr int NKV = 2 * NTILES;
constexpr int NRED = 72;

#define DEPTH_MAIN 4
#define DEPTH_MIN 2
#define START_LOADS 6
#define DEPTH_QUIET 2
#define DEPTH_WO 6
#define DEPTH_END 7
#define DEPTH_W2 5
#define KV_LEFT 2
#define EARLY_W 5
#define DBG_SKIP 0
#define W_PROMO CU_TENSOR_MAP_L2_PROMOTION_L2_128B
#define PACE_BIAS -64
#define PACE_SHIFT 8
#define MON_SLEEP 1000
#define CLEAR_AT 190
#define PROBES 3
#define Q_SLEEP 800
#define B_LAG 2
#define PROD_SLEEP 0
#define SWAP13 1
#define WQ_ROT 0
#define MBAR_LIMIT 1
#define DBG_PAD 0
#define F1_SYNC 1
#define DUMP 1
#define W2_RAMP 1
#define LP_SHIFT 5
#define LP_GAIN 0
#define DEPTH_FRAC 255
#define TWO_CNT 0
#define REREAD 1
#define PF0 0
#define CHUNK_LOG 1
#define KV0_WAIT 2
#define SKEW 0
#define KV_POLICY "evict_first"
#define KV_PROMO CU_TENSOR_MAP_L2_PROMOTION_NONE
#define EARLY_EVEN 1
#define COOP 0
#define DBG_LAND 0
#define ADAPT 0
#define HOME_MODE 1
#define POLL_DELAY 0
constexpr int WQ_PIECE = 144 * 64;
constexpr int W13_PIECE = 72 * 80;
constexpr int ROW8_PIECE = 8 * 1152;

constexpr int SM_RING = 0;
constexpr int SM_WO = SM_RING;
constexpr int SM_W3B = SM_RING + 3 * SLOT_BYTES;
constexpr int SM_W2 = SM_RING + 4 * SLOT_BYTES;
constexpr int SM_W1 = NSLOTS * SLOT_BYTES;
constexpr int SM_BAR = SM_W1 + 14 * W13_PIECE;
constexpr int SM_RED = SM_BAR + 368;
constexpr int SM_XN = SM_RED + 4096;
constexpr int XN_PITCH = 584 * 2;
constexpr int SM_ML = SM_RED + 8 * 80 * 16;
constexpr int SM_Q = SM_ML + 64;
constexpr int SM_D1 = SM_Q + 512;
constexpr int SM_ACT = SM_D1 + 512;
constexpr int SM_RED4 = SM_ACT + 192;
constexpr int SM_HS = SM_RED4 + 512;
constexpr int SM_ONES = SM_HS + 8 * 18 * 16;
constexpr int SM_PROG = SM_ONES + 16;
constexpr int SM_HOME = SM_PROG + 16;
constexpr int SM_TOTAL = SM_HOME + 144;
static_assert(SM_TOTAL <= 232448, "smem");

constexpr unsigned SENTINEL = 0xFFFFFFFFu;
constexpr float LOG2E = 1.4426950408889634f;
constexpr float SCALE = 0.08838834764831845f;
constexpr unsigned SPIN_LIMIT = 1u << 24;

}

__device__ __align__(128) unsigned g_sync[3 * 32];
__device__ __align__(128) uint2 g_pq[2][HKV][128];
constexpr uint32_t X_P3 = 0, X_P1 = 8 * 8192, X_P2 = 72 * 8192, X_PR = 216 * 8192, X_END = 232 * 8192;
constexpr uint32_t CNT_OFF = 3072;
constexpr uint32_t P4_OFF = 16384;
__device__ __forceinline__ uint32_t p2_block(int rd) { return X_P2 + (rd >> 1) * 32768 + (rd & 1) * 8192; }
static_assert(X_END <= (2u << 20), "one page");
__device__ unsigned char g_xraw[(2u << 20) + X_END];
__device__ __align__(128) unsigned g_home[NCTA];
__device__ __forceinline__ uint32_t near_of(uint32_t blk, uint32_t side) { return blk + (((__popc(blk & 0xB2000u) ^ side) & 1) << 12); }
#define TL(i) do {} while (0)
#define TLCAL(i) do {} while (0)
#define TLM(i) do {} while (0)

__device__ __forceinline__ void mbar_init(uint32_t bar, uint32_t cnt) {
    asm volatile("mbarrier.init.shared::cta.b64 [%0], %1;" ::"r"(bar), "r"(cnt) : "memory");
}
__device__ __forceinline__ void mbar_expect_tx(uint32_t bar, uint32_t bytes) {
    asm volatile("mbarrier.arrive.expect_tx.shared::cta.b64 _, [%0], %1;" ::"r"(bar), "r"(bytes) : "memory");
}
__device__ __forceinline__ void mbar_arrive(uint32_t bar) {
    asm volatile("mbarrier.arrive.shared::cta.b64 _, [%0];" ::"r"(bar) : "memory");
}
__device__ __forceinline__ void mbar_wait(uint32_t bar, uint32_t parity) {
    asm volatile("{\n.reg .pred p;\n.reg .u32 n;\nmov.u32 n, 0;\n"
                 "WAIT_LOOP:\nmbarrier.try_wait.parity.shared::cta.b64 p, [%0], %1;\n@p bra WAIT_DONE;\n"
                 "add.u32 n, n, 1;\nsetp.lt.u32 p, n, 0x1000000;\n@p bra WAIT_LOOP;\ntrap;\nWAIT_DONE:\n}"
                 ::"r"(bar), "r"(parity) : "memory");
}
__device__ __forceinline__ bool mbar_test(uint32_t bar, uint32_t parity) {
    uint32_t ok;
    asm volatile("{\n.reg .pred p;\nmbarrier.test_wait.parity.shared::cta.b64 p, [%1], %2;\nselp.u32 %0, 1, 0, p;\n}"
                 : "=r"(ok) : "r"(bar), "r"(parity) : "memory");
    return ok != 0;
}
__device__ __forceinline__ void mbar_wait_all(uint32_t bar) {
    uint32_t ok;
    unsigned n = 0;
    do {
        if (MBAR_LIMIT && ++n > SPIN_LIMIT) __trap();
        asm volatile("{\n.reg .pred p;\nmbarrier.try_wait.parity.shared::cta.b64 p, [%1], 0;\nselp.u32 %0, 1, 0, p;\n}"
                     : "=r"(ok) : "r"(bar) : "memory");
    } while (!__all_sync(0xffffffffu, ok));
    __syncwarp();
}
__device__ __forceinline__ void bar_sync(int id, int n) { asm volatile("bar.sync %0, %1;" ::"r"(id), "r"(n) : "memory"); }
__device__ __forceinline__ void bar_arrive(int id, int n) { asm volatile("bar.arrive %0, %1;" ::"r"(id), "r"(n) : "memory"); }

__device__ __forceinline__ void tma2d(uint32_t dst, const CUtensorMap* m, int c0, int c1, uint32_t bar) {
    asm volatile("cp.async.bulk.tensor.2d.shared::cluster.global.mbarrier::complete_tx::bytes [%0], [%1, {%3, %4}], [%2];"
                 ::"r"(dst), "l"(m), "r"(bar), "r"(c0), "r"(c1) : "memory");
}
__device__ __forceinline__ void tma3d(uint32_t dst, const CUtensorMap* m, int c1, uint32_t bar) {
    asm volatile("cp.async.bulk.tensor.3d.shared::cluster.global.mbarrier::complete_tx::bytes [%0], [%1, {0, %3, 0}], [%2];"
                 ::"r"(dst), "l"(m), "r"(bar), "r"(c1) : "memory");
}
__device__ __forceinline__ void tma3d_hint(uint32_t dst, const CUtensorMap* m, int c1, uint32_t bar, uint64_t pol) {
    asm volatile("cp.async.bulk.tensor.3d.shared::cluster.global.mbarrier::complete_tx::bytes.L2::cache_hint [%0], [%1, {0, %3, 0}], [%2], %4;"
                 ::"r"(dst), "l"(m), "r"(bar), "r"(c1), "l"(pol) : "memory");
}
__device__ __forceinline__ void ldsm4(uint32_t (&r)[4], uint32_t a) {
    asm volatile("ldmatrix.sync.aligned.m8n8.x4.shared.b16 {%0,%1,%2,%3}, [%4];"
                 : "=r"(r[0]), "=r"(r[1]), "=r"(r[2]), "=r"(r[3]) : "r"(a) : "memory");
}
__device__ __forceinline__ void ldsm4t(uint32_t (&r)[4], uint32_t a) {
    asm volatile("ldmatrix.sync.aligned.m8n8.x4.trans.shared.b16 {%0,%1,%2,%3}, [%4];"
                 : "=r"(r[0]), "=r"(r[1]), "=r"(r[2]), "=r"(r[3]) : "r"(a) : "memory");
}
__device__ __forceinline__ void ldsm2t(uint32_t& r0, uint32_t& r1, uint32_t a) {
    asm volatile("ldmatrix.sync.aligned.m8n8.x2.trans.shared.b16 {%0,%1}, [%2];" : "=r"(r0), "=r"(r1) : "r"(a) : "memory");
}
__device__ __forceinline__ void ldsm1t(uint32_t& r0, uint32_t a) {
    asm volatile("ldmatrix.sync.aligned.m8n8.x1.trans.shared.b16 {%0}, [%1];" : "=r"(r0) : "r"(a) : "memory");
}
__device__ __forceinline__ void ldsm1(uint32_t& r0, uint32_t a) {
    asm volatile("ldmatrix.sync.aligned.m8n8.x1.shared.b16 {%0}, [%1];" : "=r"(r0) : "r"(a) : "memory");
}
__device__ __forceinline__ void mma16816(float (&c)[4], uint32_t a0, uint32_t a1, uint32_t a2, uint32_t a3, uint32_t b0, uint32_t b1) {
    asm("mma.sync.aligned.m16n8k16.row.col.f32.bf16.bf16.f32 {%0,%1,%2,%3}, {%4,%5,%6,%7}, {%8,%9}, {%0,%1,%2,%3};"
                 : "+f"(c[0]), "+f"(c[1]), "+f"(c[2]), "+f"(c[3]) : "r"(a0), "r"(a1), "r"(a2), "r"(a3), "r"(b0), "r"(b1));
}
__device__ __forceinline__ void mma16816v(float (&c)[4], uint32_t a0, uint32_t a1, uint32_t a2, uint32_t a3, uint32_t b0, uint32_t b1) {
    asm volatile("mma.sync.aligned.m16n8k16.row.col.f32.bf16.bf16.f32 {%0,%1,%2,%3}, {%4,%5,%6,%7}, {%8,%9}, {%0,%1,%2,%3};"
                 : "+f"(c[0]), "+f"(c[1]), "+f"(c[2]), "+f"(c[3]) : "r"(a0), "r"(a1), "r"(a2), "r"(a3), "r"(b0), "r"(b1));
}
__device__ __forceinline__ float4 lds128(uint32_t a) {
    float4 v;
    asm volatile("ld.shared.v4.f32 {%0,%1,%2,%3}, [%4];" : "=f"(v.x), "=f"(v.y), "=f"(v.z), "=f"(v.w) : "r"(a) : "memory");
    return v;
}
__device__ __forceinline__ void sts64(uint32_t a, float x, float y) {
    asm volatile("st.shared.v2.f32 [%0], {%1,%2};" ::"r"(a), "f"(x), "f"(y) : "memory");
}
__device__ __forceinline__ void mma1688(float (&c)[4], uint32_t a0, uint32_t a1, uint32_t b0) {
    asm("mma.sync.aligned.m16n8k8.row.col.f32.bf16.bf16.f32 {%0,%1,%2,%3}, {%4,%5}, {%6}, {%0,%1,%2,%3};"
                 : "+f"(c[0]), "+f"(c[1]), "+f"(c[2]), "+f"(c[3]) : "r"(a0), "r"(a1), "r"(b0));
}
__device__ __forceinline__ uint32_t movm(uint32_t a) {
    uint32_t d;
    asm volatile("movmatrix.sync.aligned.m8n8.trans.b16 %0, %1;" : "=r"(d) : "r"(a));
    return d;
}
__device__ __forceinline__ uint32_t pack_bf16(float lo, float hi) {
    uint32_t d;
    asm("cvt.rn.bf16x2.f32 %0, %1, %2;" : "=r"(d) : "f"(hi), "f"(lo));
    return d;
}
__device__ __forceinline__ float bf_lo(uint32_t v) { return __uint_as_float(v << 16); }
__device__ __forceinline__ float bf_hi(uint32_t v) { return __uint_as_float(v & 0xFFFF0000u); }
__device__ __forceinline__ float bfr(float x) { return __uint_as_float(pack_bf16(0.f, x)); }
__device__ __forceinline__ float ex2(float x) { float y; asm("ex2.approx.ftz.f32 %0, %1;" : "=f"(y) : "f"(x)); return y; }
__device__ __forceinline__ float rcp(float x) { float y; asm("rcp.approx.ftz.f32 %0, %1;" : "=f"(y) : "f"(x)); return y; }
__device__ __forceinline__ float lg2(float x) { float y; asm("lg2.approx.ftz.f32 %0, %1;" : "=f"(y) : "f"(x)); return y; }

__device__ __forceinline__ uint4 ld_relaxed128(const void* p) {
    uint4 v;
    asm volatile("{\n.reg .b128 t;\n.reg .b64 lo, hi;\nld.relaxed.gpu.global.b128 t, [%4];\nmov.b128 {lo, hi}, t;\n"
                 "mov.b64 {%0, %1}, lo;\nmov.b64 {%2, %3}, hi;\n}"
                 : "=r"(v.x), "=r"(v.y), "=r"(v.z), "=r"(v.w) : "l"(p) : "memory");
    return v;
}
__device__ __forceinline__ void ld_relaxed128_if(uint4& v, const void* p, bool need) {
    asm volatile("{\n.reg .pred q;\n.reg .b128 t;\n.reg .b64 lo, hi;\nsetp.ne.u32 q, %5, 0;\nmov.b64 lo, {%0, %1};\nmov.b64 hi, {%2, %3};\n"
                 "mov.b128 t, {lo, hi};\n@q ld.relaxed.gpu.global.b128 t, [%4];\nmov.b128 {lo, hi}, t;\n"
                 "mov.b64 {%0, %1}, lo;\nmov.b64 {%2, %3}, hi;\n}"
                 : "+r"(v.x), "+r"(v.y), "+r"(v.z), "+r"(v.w) : "l"(p), "r"((unsigned)need) : "memory");
}
__device__ __forceinline__ void st_relaxed128(void* p, uint32_t x, uint32_t y, uint32_t z, uint32_t w) {
    asm volatile("{\n.reg .b128 t;\n.reg .b64 lo, hi;\nmov.b64 lo, {%1, %2};\nmov.b64 hi, {%3, %4};\nmov.b128 t, {lo, hi};\n"
                 "st.relaxed.gpu.global.b128 [%0], t;\n}"
                 ::"l"(p), "r"(x), "r"(y), "r"(z), "r"(w) : "memory");
}
__device__ __forceinline__ uint2 ld_relaxed64(const void* p) {
    uint2 v;
    asm volatile("{\n.reg .b64 t;\nld.relaxed.gpu.global.b64 t, [%2];\nmov.b64 {%0, %1}, t;\n}" : "=r"(v.x), "=r"(v.y) : "l"(p) : "memory");
    return v;
}
__device__ __forceinline__ void st_relaxed64(void* p, uint32_t x, uint32_t y) {
    asm volatile("{\n.reg .b64 t;\nmov.b64 t, {%1, %2};\nst.relaxed.gpu.global.b64 [%0], t;\n}" ::"l"(p), "r"(x), "r"(y) : "memory");
}
__device__ __forceinline__ unsigned ld_relaxed32(const void* p) {
    unsigned v;
    asm volatile("ld.relaxed.gpu.global.u32 %0, [%1];" : "=r"(v) : "l"(p) : "memory");
    return v;
}
__device__ __forceinline__ void st_relaxed32(void* p, unsigned v) {
    asm volatile("st.relaxed.gpu.global.u32 [%0], %1;" ::"l"(p), "r"(v) : "memory");
}
__device__ __forceinline__ void red_add(unsigned* p) {
    asm volatile("red.relaxed.gpu.global.add.u32 [%0], 1;" ::"l"(p) : "memory");
}
__device__ __forceinline__ bool valid4(const uint4& v) {
    return v.x != SENTINEL && v.y != SENTINEL && v.z != SENTINEL && v.w != SENTINEL;
}
__device__ __forceinline__ uint32_t not_sentinel(uint32_t u) { return u == SENTINEL ? 0x7FFF7FFFu : u; }
__device__ __forceinline__ uint4 ldg_nc128(const void* p) {
    uint4 v;
    asm volatile("ld.global.nc.L1::no_allocate.v4.u32 {%0,%1,%2,%3}, [%4];" : "=r"(v.x), "=r"(v.y), "=r"(v.z), "=r"(v.w) : "l"(p));
    return v;
}

__device__ __forceinline__ unsigned near_page(unsigned* p) {
    unsigned best0, best1;
    asm volatile("atom.relaxed.gpu.global.exch.b32 %0, [%1], 0;" : "=r"(best0) : "l"(p) : "memory");
    asm volatile("atom.relaxed.gpu.global.exch.b32 %0, [%1], 0;" : "=r"(best1) : "l"(p + 1024) : "memory");
    asm volatile("or.b32 %0, %0, 0x7fffffff;" : "+r"(best0) :: "memory");
    asm volatile("or.b32 %0, %0, 0x7fffffff;" : "+r"(best1) :: "memory");
#pragma unroll 1
    for (int i = 0; i < 2 * PROBES; i++) {
        unsigned v, t0, t1;
        asm volatile("mov.u32 %0, %%clock;" : "=r"(t0) :: "memory");
        asm volatile("atom.relaxed.gpu.global.exch.b32 %0, [%1], %2;" : "=r"(v) : "l"(p + ((i & 1) << 10)), "r"(SENTINEL) : "memory");
        asm volatile("{\n.reg .pred p;\nsetp.ne.u32 p, %1, 0x5a5a5a5a;\nmov.u32 %0, 0;\n@p mov.u32 %0, %%clock;\n}" : "=r"(t1) : "r"(v) : "memory");
        if (i & 1) best1 = min(best1, t1 - t0); else best0 = min(best0, t1 - t0);
    }
    return HOME_MODE == 1 ? best1 < best0 : HOME_MODE == 2 ? best1 >= best0 : 0;
}

__device__ __forceinline__ uint32_t finish_sum(uint32_t a, uint32_t res) {
    float2 c[8];
#pragma unroll
    for (int i = 0; i < 8; i++) asm volatile("ld.shared.v2.f32 {%0,%1}, [%2];" : "=f"(c[i].x), "=f"(c[i].y) : "r"(a + i * 64) : "memory");
    const uint32_t t = pack_bf16(((c[0].x + c[1].x) + (c[2].x + c[3].x)) + ((c[4].x + c[5].x) + (c[6].x + c[7].x)),
                                 ((c[0].y + c[1].y) + (c[2].y + c[3].y)) + ((c[4].y + c[5].y) + (c[6].y + c[7].y)));
    return pack_bf16(bf_lo(res) + bf_lo(t), bf_hi(res) + bf_hi(t));
}

enum { BAR_ALL = 1, BAR_MAIN = 2, BAR_HELP = 3, BAR_RDY = 4, BAR_INIT = 5, BAR_PROBE = 6, BAR_F1 = 7, BAR_VEC = 8, BAR_SUM = 9, BAR_OWN = 10, BAR_H = 11, BAR_P2 = 12, BAR_AUX = 13 };
#define PIN(v) asm volatile("" : "+r"(v))

__global__ void __launch_bounds__(NTHREADS, 1)
fused_decode_kernel(const __grid_constant__ CUtensorMap map_k, const __grid_constant__ CUtensorMap map_v,
                    const __grid_constant__ CUtensorMap map_wo, const __grid_constant__ CUtensorMap map_w1,
                    const __grid_constant__ CUtensorMap map_w3, const __grid_constant__ CUtensorMap map_w2,
                    const __grid_constant__ CUtensorMap map_wq, const __nv_bfloat16* __restrict__ x,
                    __nv_bfloat16* __restrict__ out) {
    extern __shared__ __align__(1024) unsigned char smem[];
    const uint32_t sb = (uint32_t)__cvta_generic_to_shared(smem);
    const int tid = threadIdx.x, lane = tid & 31;
    const int warp = __shfl_sync(0xffffffffu, tid >> 5, 0);
    const int cta = blockIdx.x;
    const int hkv = cta >> 3, r = cta & 7;
    const uint32_t bar_full = sb + SM_BAR, bar_empty = bar_full + 64, bar_w = bar_full + 128,
                   bar_l = bar_full + 160;
    volatile int* const prog = reinterpret_cast<volatile int*>(smem + SM_PROG);
    float* const red = reinterpret_cast<float*>(smem + SM_RED);
    unsigned char* const g_x = reinterpret_cast<unsigned char*>((reinterpret_cast<uintptr_t>(g_xraw) + 0x1FFFFF) & ~(uintptr_t)0x1FFFFF);
    const int g = lane >> 2, t4 = lane & 3;

    if (warp == 8) {
        if (lane == 0) TL(0);
        if (lane == 0) {
#pragma unroll
            for (int p = 0; p < 4; p++) mbar_init(bar_w + 8 * p, 1);
#pragma unroll
            for (int p = 0; p < 4; p++) {
                const int pp = WQ_ROT ? p ^ ((cta & 1) << 1) : p;
                mbar_expect_tx(bar_w + 8 * pp, WQ_PIECE);
                tma2d(sb + SM_W1 + pp * WQ_PIECE, &map_wq, cta * 32, pp * 144, bar_w + 8 * pp);
            }
        }
        __syncwarp();
        bar_arrive(0, 320);
        bar_sync(BAR_INIT, 64);
        const int f0 = (cta >> 1) * 72 + (cta & 1) * 32;
        const int early = EARLY_W + ((cta & 1) ? 0 : EARLY_EVEN);
        if (lane == 0) {
            uint64_t pol;
            asm volatile("createpolicy.fractional.L2::" KV_POLICY ".b64 %0, 1.0;" : "=l"(pol));
            const int row0 = ((r >> 2) * HKV + hkv) * SK + (r & 3) * (TILE_KEYS << CHUNK_LOG);
#pragma unroll 1
            for (int i = 0; i < NKV; i++) {
                const int slot = i & (NSLOTS - 1);
                if (i >= NSLOTS) mbar_wait(bar_empty + 8 * slot, ((i >> 3) - 1) & 1);
                const int j = i - (i < START_LOADS ? DEPTH_QUIET : prog[1]);
                if (j >= 0) mbar_wait(bar_full + 8 * (j & 7), (j >> 3) & 1);
                else if (KV0_WAIT == 1 && i < 2) mbar_wait(bar_w + 16 * i, 0);
                else if (KV0_WAIT == 2 && i == 1) mbar_wait(bar_w + 8, 0);
                prog[0] = j + 1;
                const int row = row0 + (((i >> 2) + SKEW * (cta >> 2)) & 63) * (8 * TILE_KEYS) + ((i >> 1) & 1) * TILE_KEYS;
                mbar_expect_tx(bar_full + 8 * slot, SLOT_BYTES);
                tma3d_hint(sb + SM_RING + slot * SLOT_BYTES, (i & 1) ? &map_v : &map_k, row, bar_full + 8 * slot, pol);
                if (EARLY_W && i >= 32 && i < 32 + early) {
                    const int k = i - 32;
                    mbar_expect_tx(bar_l + 32 + 8 * k, W13_PIECE);
                    tma2d(sb + SM_W1 + k * W13_PIECE, k < 8 ? &map_w1 : &map_w3, f0, slot * 72, bar_l + 32 + 8 * k);
                }
                if (i == NKV - 32) {
                    asm volatile("prefetch.tensormap [%0];" ::"l"(&map_wo) : "memory");
                    asm volatile("prefetch.tensormap [%0];" ::"l"(&map_w1) : "memory");
                    asm volatile("prefetch.tensormap [%0];" ::"l"(&map_w3) : "memory");
                    asm volatile("prefetch.tensormap [%0];" ::"l"(&map_w2) : "memory");
                }
            }
            TL(1);
            prog[0] = NKV;
        }
        __syncwarp();
        {
            const int q = lane, p = q < 4 ? q : q + early;
            const bool rows = p < 4 || p >= 20;
            const uint32_t bar = bar_l + 8 * p;
            const CUtensorMap* map = p < 4 ? &map_wo : p < 12 ? &map_w1 : p < 20 ? &map_w3 : &map_w2;
            const uint32_t dst = sb + (p < 4 ? SM_WO + p * ROW8_PIECE : p < 18 ? SM_W1 + (p - 4) * W13_PIECE
                                     : p < 20 ? SM_W3B + (p - 18) * W13_PIECE : SM_W2 + (p - 20) * ROW8_PIECE);
            const int row = p < 4 ? cta * 32 + p * 8 : p < 20 ? ((p - 4) & 7) * 72 : f0 + (p - 20) * 8;
            const int d = p < 20 ? min(DEPTH_END, DEPTH_WO + max(q - 5, 0)) : max(DEPTH_W2, min(DEPTH_END, DEPTH_WO + 15 - early) + W2_RAMP * (19 - p));
            const int qa = q - d;
            const uint32_t ga = qa >= 0 ? bar_l + 8 * (qa < 4 ? qa : qa + early) : bar_full + 8 * min(7, 7 - KV_LEFT + (q >> 1));
            const uint32_t gb = bar_empty + 8 * (p >= 20 ? 6 : 3);
            bool todo = p < 25;
            if (todo && ((p == 20 && (cta & 1)) || (DBG_SKIP & 8))) {
                mbar_arrive(bar);
                todo = false;
            }
            if (todo) mbar_expect_tx(bar, rows ? ROW8_PIECE : W13_PIECE);
            unsigned n = 0;
            constexpr bool track = false;
            while (__any_sync(0xffffffffu, todo || track)) {
                if (++n > (SPIN_LIMIT << 2)) __trap();
                if (PROD_SLEEP) __nanosleep(PROD_SLEEP);
                if (todo && ((DUMP && prog[2]) || mbar_test(ga, qa >= 0 ? 0 : 1)) && mbar_test(gb, 1)) {
                    if (rows) tma3d(dst, map, row, bar); else tma2d(dst, map, f0, row, bar);
                    todo = false;
                }
            }
            if (lane == 0) TL(2);
        }
        return;
    }

    if (warp > 8) {
        if (warp == 9) {
            if (lane == 0) {
#pragma unroll 1
                for (int i = 0; i < 8; i++) { mbar_init(bar_full + 8 * i, 1); mbar_init(bar_empty + 8 * i, 4); }
                prog[0] = 0; prog[1] = DEPTH_MAIN; prog[2] = 0;
#pragma unroll 5
                for (int i = 0; i < 25; i++) mbar_init(bar_l + 8 * i, 1);
                *reinterpret_cast<uint4*>(smem + SM_ONES) = make_uint4(0x3F803F80u, 0x3F803F80u, 0x3F803F80u, 0x3F803F80u);
            }
            __syncwarp();
            bar_arrive(BAR_INIT, 64);
            bar_arrive(0, 320);
        }
        if (lane == 0) {
            const uint32_t blk = X_PR + (cta & 15) * 8192;
            smem[SM_HOME + 128 + warp - 9] = (near_page(reinterpret_cast<unsigned*>(g_x + blk + (cta >> 4) * 512 + (warp - 9) * 128)) ^ __popc(blk & 0xB2000u)) & 1;
            if (warp == 10) TL(26);
        }
        __syncwarp();
        bar_sync(BAR_PROBE, 224);
        uint32_t res = 0, rs4 = sb + SM_RED4 + (lane & 7) * 8;
        const unsigned side = (smem[SM_HOME + 128] + smem[SM_HOME + 129] + smem[SM_HOME + 130]) >> 1;
        if (warp == 9) {
            if (lane == 0) {
                TLCAL(30);
                const uint32_t cnt = near_of(X_P3, TWO_CNT ? side : 0) + CNT_OFF;
                int last = 0, cur, slow = 0;
                unsigned n = 0;
                do {
                    if (++n > SPIN_LIMIT) __trap();
                    __nanosleep(MON_SLEEP);
                    cur = prog[0];
                    const int tot = (int)atomicAdd(reinterpret_cast<unsigned*>(g_x + cnt), (unsigned)(cur - last));
                    if (TWO_CNT) atomicAdd(reinterpret_cast<unsigned*>(g_x + (cnt ^ 4096)), (unsigned)(cur - last));
                    last = cur;
                    const int lead = (REREAD ? prog[tot >> 30] : cur) * NCTA - tot - PACE_BIAS;
                    slow += lead - (slow >> LP_SHIFT);
                    prog[1] = max(DEPTH_MIN, min(NSLOTS, DEPTH_MAIN + ((DEPTH_FRAC - lead - LP_GAIN * (slow >> LP_SHIFT)) >> PACE_SHIFT)));
                } while (cur < NKV - 8);
                TLCAL(28);
            }
            __syncwarp();
        } else if (warp == 10) {
            const unsigned char* pp = g_x + near_of(X_P1 + (cta >> 1) * 8192, side) + (cta & 1) * 2048 + (lane >> 4) * 1024 + (lane & 15) * 16;
            uint32_t oa = sb + SM_ACT + (lane >> 4) * 80 + 16 + (lane & 15) * 4;
            PIN(oa);
            uint4 v[4];
#pragma unroll
            for (int i = 0; i < 4; i++) v[i] = make_uint4(0, 0, 0, SENTINEL);
            unsigned n = 0;
            bar_sync(BAR_OWN, 160);
            do {
                if (++n > SPIN_LIMIT) __trap();
#pragma unroll
                for (int i = 0; i < 4; i++) ld_relaxed128_if(v[i], pp + i * 256, v[i].w == SENTINEL);
            } while (__any_sync(0xffffffffu, v[0].w == SENTINEL || v[1].w == SENTINEL || v[2].w == SENTINEL || v[3].w == SENTINEL));
            TLM(7);
            const float W = fmaxf(fmaxf(__uint_as_float(v[0].z), __uint_as_float(v[1].z)), fmaxf(__uint_as_float(v[2].z), __uint_as_float(v[3].z)));
            float e[4];
#pragma unroll
            for (int i = 0; i < 4; i++) e[i] = ex2((__uint_as_float(v[i].z) - W) * LOG2E);
            const float inv = rcp(fmaf(e[0], __uint_as_float(v[0].w), e[1] * __uint_as_float(v[1].w)) + fmaf(e[2], __uint_as_float(v[2].w), e[3] * __uint_as_float(v[3].w)));
            const float o0 = fmaf(e[0], __uint_as_float(v[0].x), e[1] * __uint_as_float(v[1].x)) + fmaf(e[2], __uint_as_float(v[2].x), e[3] * __uint_as_float(v[3].x));
            const float o1 = fmaf(e[0], __uint_as_float(v[0].y), e[1] * __uint_as_float(v[1].y)) + fmaf(e[2], __uint_as_float(v[2].y), e[3] * __uint_as_float(v[3].y));
            asm volatile("st.shared.u32 [%0], %1;" ::"r"(oa), "r"(pack_bf16(o0 * inv, o1 * inv)) : "memory");
            __syncwarp();
            bar_arrive(BAR_VEC, 288);
            if (DUMP > 1) { __nanosleep(DUMP); prog[2] = 1; }
        } else if (cta < NRED) {
            res = ld_relaxed32(reinterpret_cast<const uint32_t*>(x + (g & 1) * D_MODEL + cta * 8) + t4);
            unsigned char* hp = g_x + X_P3 + (lane >> 3) * 16384 + cta * 32 + (lane & 7) * 4;
            PIN(res); PIN(rs4);
            bar_sync(BAR_SUM, 288);
            res = finish_sum(rs4, res);
#pragma unroll
            for (int i = 0; i < 4; i++) st_relaxed32(hp + i * 4096, res);
            if (lane == 0) TL(9);
        }
        if (warp < 11) {
            const uint32_t off = ((warp - 9) * 72 + lane) * 16;
            const unsigned char* hp = g_x + near_of(X_P3 + (cta & 7) * 8192, side) + off;
            uint4 u[3];
            bool need[3];
#pragma unroll
            for (int i = 0; i < 3; i++) { u[i] = make_uint4(0, 0, 0, 0); need[i] = lane < 24; }
            bar_sync(BAR_P2, 352);
            unsigned n = 0;
            do {
                if (++n > SPIN_LIMIT) __trap();
#pragma unroll
                for (int i = 0; i < 3; i++) ld_relaxed128_if(u[i], hp + i * 384, need[i]);
#pragma unroll
                for (int i = 0; i < 3; i++) need[i] = !valid4(u[i]);
                if (DUMP == 1 && lane < 24 && !(need[0] && need[1] && need[2])) prog[2] = 1;
            } while (__any_sync(0xffffffffu, need[0] || need[1] || need[2]));
            if (lane < 24) {
#pragma unroll
                for (int i = 0; i < 3; i++) *reinterpret_cast<uint4*>(smem + SM_HS + off + i * 384) = u[i];
            }
            __syncwarp();
            TLM(11);
            bar_arrive(BAR_H, 320);
            float sm = 0.f, sq = 0.f;
#pragma unroll
            for (int i = 0; i < 3; i++) {
                const uint32_t w[4] = {u[i].x, u[i].y, u[i].z, u[i].w};
                float s1 = 0.f, s2 = 0.f;
#pragma unroll
                for (int k = 0; k < 4; k++) {
                    const float lo = bf_lo(w[k]), hi = bf_hi(w[k]);
                    s1 += lo + hi;
                    s2 = fmaf(lo, lo, fmaf(hi, hi, s2));
                }
                sm += s1; sq += s2;
            }
#pragma unroll
            for (int o = 2; o < 32; o <<= 1) {
                sm += __shfl_xor_sync(0xffffffffu, sm, o);
                sq += __shfl_xor_sync(0xffffffffu, sq, o);
            }
            if (lane < 2) *reinterpret_cast<float2*>(smem + SM_ML + lane * 16 + (warp - 9) * 8) = make_float2(sm, sq);
        } else {
            bar_arrive(BAR_P2, 352);
        }
        bar_sync(BAR_AUX, 96);
        const int at = tid - 288, bb = at & 1;
        uint32_t ra = sb + SM_RED + min(at, 79) * 16;
        uint32_t wa = sb + SM_ACT + bb * 80 + (at >> 1) * 2;
        const float4 st = lds128(sb + SM_ML + bb * 16);
        const float mean = (st.x + st.z) * (1.f / D_MODEL);
        const float var = fmaxf(fmaf(-mean, mean, (st.y + st.w) * (1.f / D_MODEL)), 0.f);
        float mb = bfr(mean), sd, isd;
        asm("sqrt.approx.ftz.f32 %0, %1;" : "=f"(sd) : "f"(bfr(bfr(var) + 1e-5f)));
        asm volatile("rcp.approx.ftz.f32 %0, %1;" : "=f"(isd) : "f"(bfr(sd)));
        bar_sync(BAR_F1, 352);
        float4 u[8];
#pragma unroll
        for (int wv = 0; wv < 8; wv++) u[wv] = lds128(ra + wv * 80 * 16);
#pragma unroll
        for (int d = 4; d; d >>= 1) {
#pragma unroll
            for (int i = 0; i < d; i++) { u[i].x += u[i + d].x; u[i].y += u[i + d].y; u[i].z += u[i + d].z; }
        }
        const float v0 = u[0].x, v1 = u[0].y, cs = u[0].z;
        const float ov = __shfl_xor_sync(0xffffffffu, bb ? v0 : v1, 1), ocs = __shfl_xor_sync(0xffffffffu, cs, 1);
        const float gt = bfr(fmaf(-mb, bb ? ocs : cs, bb ? ov : v0) * isd);
        const float up = bfr(fmaf(-mb, bb ? cs : ocs, bb ? v1 : ov) * isd);
        const float act = bfr(gt * rcp(1.f + ex2(-gt * LOG2E))) * up;
        if (at < 80) asm volatile("st.shared.u16 [%0], %1;" ::"r"(wa), "h"((unsigned short)pack_bf16(act, 0.f)) : "memory");
        TLM(12);
        bar_arrive(BAR_VEC, 352);
        if (warp == 11 && cta < NRED) {
            uint32_t* op = reinterpret_cast<uint32_t*>(out + (g & 1) * D_MODEL + cta * 8) + t4;
            bar_sync(BAR_SUM, 288);
            res = finish_sum(rs4, res);
            if (lane < 8) *op = res;
            if (cta == 0 && lane == 0) {
                red_add(&g_sync[0]);
                st_relaxed32(&g_sync[32], 0);
                st_relaxed32(g_x + X_P3 + CNT_OFF, 0);
                st_relaxed32(g_x + X_P3 + 4096 + CNT_OFF, 0);
            }
            if (lane == 0) TL(14);
        }
        return;
    }

    unsigned tag;
    {
        const uint32_t* xp = reinterpret_cast<const uint32_t*>(x + (warp >> 2) * D_MODEL);
        uint32_t xu[9], xo[3];
#pragma unroll
        for (int i = 0; i < 9; i++) xu[i] = __ldg(xp + lane + 32 * i);
        tag = ld_relaxed32(&g_sync[0]) + 1;
        const int wq4 = warp & 3;
        xo[0] = wq4 == 0 ? xu[0] : wq4 == 1 ? xu[1] : wq4 == 2 ? xu[2] : xu[3];
        xo[1] = wq4 == 0 ? xu[4] : wq4 == 1 ? xu[5] : wq4 == 2 ? xu[6] : xu[7];
        xo[2] = xu[8];
        float s = 0.f;
#pragma unroll
        for (int i = 0; i < 9; i++) s += bf_lo(xu[i]) + bf_hi(xu[i]);
#pragma unroll
        for (int o = 16; o; o >>= 1) s += __shfl_xor_sync(0xffffffffu, s, o);
        const float mean = __fdiv_rn(s, (float)D_MODEL);
        float q2 = 0.f;
#pragma unroll
        for (int i = 0; i < 9; i++) {
            const float d0 = bf_lo(xu[i]) - mean, d1 = bf_hi(xu[i]) - mean;
            q2 = fmaf(d0, d0, fmaf(d1, d1, q2));
        }
#pragma unroll
        for (int o = 16; o; o >>= 1) q2 += __shfl_xor_sync(0xffffffffu, q2, o);
        const float mb = bfr(mean);
        const float sd = bfr(__fsqrt_rn(bfr(bfr(__fdiv_rn(q2, (float)D_MODEL)) + 1e-5f)));
#pragma unroll 1
        for (int i = 0; i < 3; i++) {
            const uint32_t u = i == 0 ? xo[0] : i == 1 ? xo[1] : xo[2];
            const int wi = i < 2 ? 4 * i + wq4 : 8;
            *reinterpret_cast<uint32_t*>(smem + SM_XN + (warp >> 2) * XN_PITCH + 4 * (lane + 32 * wi)) =
                pack_bf16(__fdiv_rn(bfr(bf_lo(u) - mb), sd), __fdiv_rn(bfr(bf_hi(u) - mb), sd));
        }
        bar_sync(0, 320);
        uint32_t xb[12];
        const uint32_t xa = sb + SM_XN + (lane & 1) * XN_PITCH + (warp * 72 + 8 * (lane >> 3)) * 2;
        ldsm4(*reinterpret_cast<uint32_t(*)[4]>(&xb[0]), xa);
        ldsm4(*reinterpret_cast<uint32_t(*)[4]>(&xb[4]), xa + 64);
        ldsm1(xb[8], xa + 128);
        mbar_wait(bar_w + 8 * (warp >> 1), 0);
        const uint32_t wa = sb + SM_W1 + (warp * 72 + (lane & 7) + 8 * (lane >> 4)) * 64;
        float qa[2][4];
#pragma unroll
        for (int j = 0; j < 2; j++) {
            const uint32_t ad = wa + (((2 * j + ((lane >> 3) & 1)) ^ ((lane >> 1) & 3)) << 4);
            qa[j][0] = qa[j][1] = qa[j][2] = qa[j][3] = 0.f;
#pragma unroll
            for (int ks = 0; ks < 4; ks++) {
                uint32_t a4[4];
                ldsm4t(a4, ad + ks * 16 * 64);
                mma16816(qa[j], a4[0], a4[1], a4[2], a4[3], xb[2 * ks], xb[2 * ks + 1]);
            }
            uint32_t a0, a1;
            ldsm2t(a0, a1, ad + 64 * 64);
            mma1688(qa[j], a0, a1, xb[8]);
        }
#pragma unroll
        for (int j = 0; j < 2; j++) {
            const float lo = (t4 & 1) ? qa[j][1] : qa[j][0], hi = (t4 & 1) ? qa[j][3] : qa[j][2];
            red[warp * 64 + (t4 & 1) * 32 + 16 * j + g + 8 * (t4 >> 1)] = (t4 & 2) ? hi : lo;
        }
        bar_sync(BAR_ALL, 256);
        if (warp == 0) {
            float s0 = 0.f, s1 = 0.f;
#pragma unroll
            for (int wv = 0; wv < 8; wv++) {
                const float2 v = *reinterpret_cast<const float2*>(red + wv * 64 + lane * 2);
                s0 += v.x; s1 += v.y;
            }
            st_relaxed64(&g_pq[lane >> 4][hkv][r * 16 + (lane & 15)], pack_bf16(s0, s1), tag);
            if (lane == 0) TL(3);
        }
    }

    if (warp < 4) {
        float* const ml = reinterpret_cast<float*>(smem + SM_ML);
        uint32_t* const qs = reinterpret_cast<uint32_t*>(smem + SM_Q);
        {
            uint2 v;
            unsigned n = 0;
            do {
                if (++n > SPIN_LIMIT) __trap();
                __nanosleep(Q_SLEEP);
                v = ld_relaxed64(&g_pq[r >> 2][hkv][tid]);
            } while (__any_sync(0xffffffffu, v.y != tag));
            qs[tid] = v.x;
            bar_sync(BAR_MAIN, 128);
        }
        if (tid == 0) TL(4);
        uint32_t koff[4], voff[4];
        {
            const int l7 = lane & 7;
            const uint32_t kb = (warp * 16 + l7 + 8 * ((lane >> 3) & 1)) * 128;
            const uint32_t vb = (warp * 16 + l7 + 8 * (lane >> 4)) * 128;
#pragma unroll
            for (int i = 0; i < 4; i++) {
                koff[i] = sb + SM_RING + kb + (((2 * i + (lane >> 4)) ^ l7) << 4);
                voff[i] = sb + SM_RING + SLOT_BYTES + vb + (((2 * i + ((lane >> 3) & 1)) ^ l7) << 4);
            }
        }
        {
            uint32_t qb[8][2];
#pragma unroll
            for (int ks = 0; ks < 8; ks++) {
                qb[ks][0] = qs[(g & 1) * 64 + ks * 8 + t4];
                qb[ks][1] = qs[(g & 1) * 64 + ks * 8 + 4 + t4];
            }
            float o[8][4];
#pragma unroll
            for (int i = 0; i < 8; i++) { o[i][0] = o[i][1] = o[i][2] = o[i][3] = 0.f; }
            float m0 = -INFINITY, m1 = -INFINITY, l0 = 0.f, l1 = 0.f;
#pragma unroll 1
            for (int t = 0; t < NTILES; t++) {
                const int slot = (2 * t) & (NSLOTS - 1);
                const uint32_t ph = (t >> 2) & 1;
                const uint32_t so = slot * SLOT_BYTES;
                mbar_wait(bar_full + 8 * slot, ph);
                uint32_t a[8][4];
#pragma unroll
                for (int ks = 0; ks < 8; ks++) ldsm4(a[ks], koff[ks & 3] + so + (ks >> 2) * 8192);
                __syncwarp();
                if (lane == 0) mbar_arrive(bar_empty + 8 * slot);
                float c[4] = {0.f, 0.f, 0.f, 0.f}, c2[4] = {0.f, 0.f, 0.f, 0.f};
#pragma unroll
                for (int ks = 0; ks < 8; ks += 2) {
                    mma16816(c, a[ks][0], a[ks][1], a[ks][2], a[ks][3], qb[ks][0], qb[ks][1]);
                    mma16816(c2, a[ks + 1][0], a[ks + 1][1], a[ks + 1][2], a[ks + 1][3], qb[ks + 1][0], qb[ks + 1][1]);
                }
                uint32_t u0 = pack_bf16(c[0] + c2[0], c[1] + c2[1]), u1 = pack_bf16(c[2] + c2[2], c[3] + c2[3]);
                u0 = pack_bf16(bf_lo(u0) * SCALE, bf_hi(u0) * SCALE);
                u1 = pack_bf16(bf_lo(u1) * SCALE, bf_hi(u1) * SCALE);
                const float s0 = bf_lo(u0), s1 = bf_hi(u0), s2 = bf_lo(u1), s3 = bf_hi(u1);
                float x0 = fmaxf(s0, s2), x1 = fmaxf(s1, s3);
                if (__any_sync(0xffffffffu, x0 > m0 || x1 > m1)) {
#pragma unroll
                    for (int of = 4; of < 32; of <<= 1) {
                        x0 = fmaxf(x0, __shfl_xor_sync(0xffffffffu, x0, of));
                        x1 = fmaxf(x1, __shfl_xor_sync(0xffffffffu, x1, of));
                    }
                    x0 = fmaxf(m0, x0); x1 = fmaxf(m1, x1);
                    const float al0 = ex2((m0 - x0) * LOG2E), al1 = ex2((m1 - x1) * LOG2E);
                    m0 = x0; m1 = x1;
                    l0 *= al0; l1 *= al1;
#pragma unroll
                    for (int i = 0; i < 8; i++) { o[i][0] *= al0; o[i][1] *= al1; o[i][2] *= al0; o[i][3] *= al1; }
                }
                const float p0 = ex2((s0 - m0) * LOG2E), p1 = ex2((s1 - m1) * LOG2E);
                const float p2 = ex2((s2 - m0) * LOG2E), p3 = ex2((s3 - m1) * LOG2E);
                l0 += p0 + p2; l1 += p1 + p3;
                const uint32_t pb0 = movm(pack_bf16(p0, p1)), pb1 = movm(pack_bf16(p2, p3));
                mbar_wait(bar_full + 8 * slot + 8, ph);
#pragma unroll
                for (int mt = 0; mt < 8; mt++) ldsm4t(a[mt], voff[mt & 3] + so + (mt >> 2) * 8192);
                __syncwarp();
                if (lane == 0) mbar_arrive(bar_empty + 8 * slot + 8);
#pragma unroll
                for (int mt = 0; mt < 8; mt++) mma16816(o[mt], a[mt][0], a[mt][1], a[mt][2], a[mt][3], pb0, pb1);
            }
            TLM(5);
#pragma unroll
            for (int of = 4; of < 32; of <<= 1) {
                l0 += __shfl_xor_sync(0xffffffffu, l0, of);
                l1 += __shfl_xor_sync(0xffffffffu, l1, of);
            }
            if (lane < 2) *reinterpret_cast<float2*>(ml + lane * 8 + warp * 2) = lane ? make_float2(m1, l1) : make_float2(m0, l0);
            {
                float* dst = red + warp * 288 + (t4 & 1) * 144 + g + 8 * (t4 >> 1);
#pragma unroll
                for (int mt = 0; mt < 8; mt++) {
                    const float lo = (t4 & 1) ? o[mt][1] : o[mt][0], hi = (t4 & 1) ? o[mt][3] : o[mt][2];
                    dst[16 * mt] = (t4 & 2) ? hi : lo;
                }
            }
            bar_sync(BAR_RDY, 256);
            bar_arrive(BAR_OWN, 160);
            {
                const int h = tid >> 6, j = tid & 63;
                const float4 w01 = *reinterpret_cast<const float4*>(ml + h * 8), w23 = *reinterpret_cast<const float4*>(ml + h * 8 + 4);
                const float* op = red + h * 144 + 2 * j;
                const float2 v0 = *reinterpret_cast<const float2*>(op), v1 = *reinterpret_cast<const float2*>(op + 288);
                const float2 v2 = *reinterpret_cast<const float2*>(op + 576), v3 = *reinterpret_cast<const float2*>(op + 864);
                const uint32_t dst1 = reinterpret_cast<const uint32_t*>(smem + SM_D1)[tid];
                const float M = fmaxf(fmaxf(w01.x, w01.z), fmaxf(w23.x, w23.z));
                const float e0 = ex2((w01.x - M) * LOG2E), e1 = ex2((w01.z - M) * LOG2E);
                const float e2 = ex2((w23.x - M) * LOG2E), e3 = ex2((w23.z - M) * LOG2E);
                const float L = fmaf(e0, w01.y, e1 * w01.w) + fmaf(e2, w23.y, e3 * w23.w);
                const float o0 = fmaf(e0, v0.x, e1 * v1.x) + fmaf(e2, v2.x, e3 * v3.x);
                const float o1 = fmaf(e0, v0.y, e1 * v1.y) + fmaf(e2, v2.y, e3 * v3.y);
                st_relaxed128(g_x + dst1, __float_as_uint(o0), __float_as_uint(o1), __float_as_uint(M), __float_as_uint(L));
            }
            TLM(6);
        }
    } else {
        const int ht = tid - 128;
        bar_sync(BAR_PROBE, 224);
        const unsigned side = (smem[SM_HOME + 128] + smem[SM_HOME + 129] + smem[SM_HOME + 130]) >> 1;
        unsigned n = 0;
        while (prog[0] < CLEAR_AT) {
            if (++n > SPIN_LIMIT) __trap();
            __nanosleep(1000);
        }
        st_relaxed128(g_x + near_of(X_P1 + (cta >> 1) * 8192, side) + (cta & 1) * 2048 + ht * 16, SENTINEL, SENTINEL, SENTINEL, SENTINEL);
        if (cta < NRED) {
            unsigned char* p = g_x + near_of(p2_block(cta), side) + ht * 16;
#pragma unroll
            for (int i = 0; i < 4; i++) st_relaxed128(p + (i >> 1) * P4_OFF + (i & 1) * 2048, SENTINEL, SENTINEL, SENTINEL, SENTINEL);
        } else if (cta < NRED + 16) {
            unsigned char* p = g_x + X_P3 + (cta - NRED) * 4096 + ht * 16;
            st_relaxed128(p, SENTINEL, SENTINEL, SENTINEL, SENTINEL);
            if (ht < 16) st_relaxed128(p + 2048, SENTINEL, SENTINEL, SENTINEL, SENTINEL);
        }
        if (ht == 0) st_relaxed32(&g_home[cta], side | (DBG_TIMELINE ? *reinterpret_cast<unsigned*>(smem + SM_HOME + 128) << 8 : 0));
        __threadfence();
        bar_sync(BAR_HELP, 128);
        if (ht == 0) {
            red_add(&g_sync[32]);
            while (ld_relaxed32(&g_sync[32]) < NCTA) {
                if (++n > SPIN_LIMIT) __trap();
                __nanosleep(2000);
            }
            __threadfence();
        }
        bar_sync(BAR_HELP, 128);
        smem[SM_HOME + ht] = (unsigned char)ld_relaxed32(&g_home[ht]);
        bar_sync(BAR_HELP, 128);
        const int rd = hkv * 8 + (ht >> 4);
        reinterpret_cast<uint32_t*>(smem + SM_D1)[ht] =
            near_of(X_P1 + (rd >> 1) * 8192, smem[SM_HOME + rd]) + (rd & 1) * 2048 + r * 256 + (ht & 15) * 16;
        if (ht == 0) TL(25);
        if (DBG_PAD) {
            float pa = ht, pb = 1.0001f;
#pragma unroll
            for (int i = 0; i < DBG_PAD; i++) asm volatile("fma.rn.f32 %0, %0, %1, %1;" : "+f"(pa) : "f"(pb));
            if (pa == 12345.f) smem[SM_HOME + 140] = 1;
        }
        bar_arrive(BAR_RDY, 256);
    }

    uint32_t wad[5], dst[3];
#pragma unroll
    for (int j = 0; j < 5; j++) {
        const int nt = warp * 9 + min(2 * j + ((lane >> 3) & 1), 8);
        wad[j] = sb + SM_WO + (lane >> 4) * ROW8_PIECE + (nt >> 3) * 1024 + (lane & 7) * 128 + (((nt ^ lane) & 7) << 4);
    }
#pragma unroll
    for (int i = 0; i < 3; i++) {
        const int rd = min(warp * 9 + 4 * i + t4, NRED - 1);
        dst[i] = near_of(p2_block(rd), smem[SM_HOME + rd]) + cta * 32 + g * 4;
    }
    const uint32_t myside = smem[SM_HOME + cta];
    uint32_t src = near_of(p2_block(cta), myside) + tid * 16;
    uint32_t vad = sb + SM_ACT + (lane & 1) * 80 + (lane >> 3) * 16;
    uint32_t rd4 = sb + SM_RED4 + (warp * 16 + (lane & 8) + (lane & 1) * 4 + (lane & 2) + ((lane >> 2) & 1)) * 4;
    uint32_t wbar = bar_l + (lane & 1) * 8;
#pragma unroll 1
    for (int pass = 0;; pass++) {
#pragma unroll
        for (int j = 0; j < 5; j++) PIN(wad[j]);
        PIN(dst[0]); PIN(dst[1]); PIN(dst[2]); PIN(src); PIN(vad); PIN(rd4);
        const bool k0 = pass && !(cta & 1);
        uint32_t w0[5][2], wp[5][4], wq[5][4];
        mbar_wait_all(pass && t4 == 2 ? wbar - 8 : wbar);
#pragma unroll
        for (int j = 0; j < 5; j++) ldsm4t(wp[j], wad[j]);
        if (k0) {
#pragma unroll
            for (int j = 0; j < 5; j++) ldsm2t(w0[j][0], w0[j][1], wad[j] - ROW8_PIECE);
        }
        if (!ADAPT) mbar_wait_all(wbar + 16);
        const bool have = !ADAPT || (ADAPT == 1 && __all_sync(0xffffffffu, mbar_test(wbar + 16, 0)));
        if (have) {
#pragma unroll
            for (int j = 0; j < 5; j++) ldsm4t(wq[j], wad[j] + 2 * ROW8_PIECE);
        }
        if (pass) TLM(16); else TLM(15);
        bar_sync(BAR_VEC, pass ? 352 : 288);
        uint32_t vb[4], v0;
        ldsm4(vb, vad + 16);
        ldsm1(v0, vad);
        float z[5][4];
#pragma unroll
        for (int j = 0; j < 5; j++) {
            z[j][0] = z[j][1] = z[j][2] = z[j][3] = 0.f;
            mma16816v(z[j], wp[j][0], wp[j][1], wp[j][2], wp[j][3], vb[0], vb[1]);
        }
        if (k0) {
#pragma unroll
            for (int j = 0; j < 5; j++) mma1688(z[j], w0[j][0], w0[j][1], v0);
        }
        if (!have) {
            mbar_wait_all(wbar + 16);
#pragma unroll
            for (int j = 0; j < 5; j++) ldsm4t(wq[j], wad[j] + 2 * ROW8_PIECE);
        }
#pragma unroll
        for (int j = 0; j < 5; j++) mma16816(z[j], wq[j][0], wq[j][1], wq[j][2], wq[j][3], vb[2], vb[3]);
#pragma unroll
        for (int i = 0; i < 2; i++) {
            const uint32_t lo = (t4 & 1) ? pack_bf16(z[2 * i][2], z[2 * i][3]) : pack_bf16(z[2 * i][0], z[2 * i][1]);
            const uint32_t hi = (t4 & 1) ? pack_bf16(z[2 * i + 1][2], z[2 * i + 1][3]) : pack_bf16(z[2 * i + 1][0], z[2 * i + 1][1]);
            st_relaxed32(g_x + dst[i], (t4 & 2) ? hi : lo);
        }
        if (t4 == 0) st_relaxed32(g_x + dst[2], pack_bf16(z[4][0], z[4][1]));
        if (pass) TLM(13); else TLM(8);
        uint32_t fa[5][18];
        const uint32_t w1a = sb + SM_W1 + (warp * 72 + (lane & 7) + 8 * (lane >> 4)) * 80 + ((lane >> 3) & 1) * 16;
        auto load_w1 = [&]() {
            mbar_wait(bar_l + 8 * (4 + warp), 0);
#pragma unroll
            for (int j = 0; j < 2; j++) {
#pragma unroll
                for (int ks = 0; ks < 4; ks++) ldsm4t(*reinterpret_cast<uint32_t(*)[4]>(&fa[j][ks * 4]), w1a + j * 32 + ks * 16 * 80);
                ldsm2t(fa[j][16], fa[j][17], w1a + j * 32 + 64 * 80);
            }
        };
        if (EARLY_W >= 8 && !pass) load_w1();
        if (cta < NRED) {
            if (POLL_DELAY) { const uint32_t t0 = clock(); while (clock() - t0 < POLL_DELAY) {} }
            uint4 v = make_uint4(0, 0, 0, 0);
            bool need = true;
            unsigned n = 0;
            do {
                if (++n > SPIN_LIMIT) __trap();
                ld_relaxed128_if(v, g_x + src, need);
                need = !valid4(v);
            } while (__any_sync(0xffffffffu, need));
            if (pass) TLM(22); else TLM(21);
            const bool k1 = lane & 2, k2 = lane & 4, k3 = lane & 8;
            const uint32_t u0 = k1 ? v.z : v.x, u1 = k1 ? v.w : v.y;
            const uint32_t y0 = __shfl_xor_sync(0xffffffffu, k1 ? v.x : v.z, 2), y1 = __shfl_xor_sync(0xffffffffu, k1 ? v.y : v.w, 2);
            const float s0 = bf_lo(u0) + bf_lo(y0), s1 = bf_hi(u0) + bf_hi(y0), s2 = bf_lo(u1) + bf_lo(y1), s3 = bf_hi(u1) + bf_hi(y1);
            const float a0 = (k2 ? s2 : s0) + __shfl_xor_sync(0xffffffffu, k2 ? s0 : s2, 4);
            const float a1 = (k2 ? s3 : s1) + __shfl_xor_sync(0xffffffffu, k2 ? s1 : s3, 4);
            float a = (k3 ? a1 : a0) + __shfl_xor_sync(0xffffffffu, k3 ? a0 : a1, 8);
            a += __shfl_xor_sync(0xffffffffu, a, 16);
            if (lane < 16) asm volatile("st.shared.f32 [%0], %1;" ::"r"(rd4), "f"(a) : "memory");
            __syncwarp();
            bar_arrive(BAR_SUM, 288);
        }
        if (pass) break;
        bar_sync(BAR_P2, 352);

        {
            const uint32_t w3r = sb + (warp < 6 ? SM_W1 + (8 + warp) * W13_PIECE : SM_W3B + (warp - 6) * W13_PIECE) + ((lane & 7) + 8 * (lane >> 4)) * 80;
            const uint32_t w3a = w3r + ((lane >> 3) & 1) * 16;
            const uint32_t wma = ((lane >> 3) & 1) ? w3r + 64 : w1a + 64;
            if (EARLY_W < 8) load_w1();
            mbar_wait(bar_l + 8 * (12 + warp), 0);
#pragma unroll
            for (int j = 2; j < 5; j++) {
                const uint32_t base = j < 4 ? w3a + (j - 2) * 32 : wma;
#pragma unroll
                for (int ks = 0; ks < 4; ks++) ldsm4t(*reinterpret_cast<uint32_t(*)[4]>(&fa[j][ks * 4]), base + ks * 16 * 80);
                ldsm2t(fa[j][16], fa[j][17], base + 64 * 80);
            }
        }
        TLM(10);
        const bool data = (lane & 7) < 2;
        uint32_t ha = data ? sb + SM_HS + (warp * 18 + (lane >> 3) * 2 + (lane & 1)) * 16 : sb + SM_ONES;
        uint32_t hs = data ? 128 : 0;
        uint32_t rd1 = sb + SM_RED + (warp * 80 + 2 * g) * 16 + 8 * t4;
        PIN(ha); PIN(hs); PIN(rd1);
        bar_sync(BAR_H, 320);
        uint32_t hb[12];
        ldsm4(*reinterpret_cast<uint32_t(*)[4]>(&hb[0]), ha);
        ldsm4(*reinterpret_cast<uint32_t(*)[4]>(&hb[4]), ha + hs);
        ldsm1(hb[8], ha + 2 * hs);
        float gu[5][4];
#pragma unroll
        for (int j = 0; j < 5; j++) { gu[j][0] = gu[j][1] = gu[j][2] = gu[j][3] = 0.f; }
#pragma unroll
        for (int ks = 0; ks < 4; ks++) {
#pragma unroll
            for (int j = 0; j < 5; j++)
                mma16816(gu[j], fa[j][ks * 4], fa[j][ks * 4 + 1], fa[j][ks * 4 + 2], fa[j][ks * 4 + 3], hb[2 * ks], hb[2 * ks + 1]);
        }
#pragma unroll
        for (int j = 0; j < 5; j++) mma1688(gu[j], fa[j][16], fa[j][17], hb[8]);
        if (t4 < 2) {
#pragma unroll
            for (int j = 0; j < 4; j++) {
                sts64(rd1 + ((j & 1) * 32 + (j >> 1)) * 16, gu[j][0], gu[j][1]);
                sts64(rd1 + ((j & 1) * 32 + 16 + (j >> 1)) * 16, gu[j][2], gu[j][3]);
            }
            sts64(rd1 + 64 * 16, gu[4][0], gu[4][1]);
            sts64(rd1 + 65 * 16, gu[4][2], gu[4][3]);
        }
        __syncwarp();
        TLM(23);
        if (F1_SYNC) bar_sync(BAR_F1, 352); else bar_arrive(BAR_F1, 352);
#pragma unroll
        for (int j = 0; j < 5; j++) wad[j] += SM_W2 + ROW8_PIECE - SM_WO;
        dst[0] += P4_OFF; dst[1] += P4_OFF; dst[2] += P4_OFF; src += P4_OFF;
        wbar += 8 * 21;
    }
}

typedef CUresult (*EncodeTiledFn)(CUtensorMap*, CUtensorMapDataType, cuuint32_t, void*, const cuuint64_t*, const cuuint64_t*,
                                  const cuuint32_t*, const cuuint32_t*, CUtensorMapInterleave, CUtensorMapSwizzle,
                                  CUtensorMapL2promotion, CUtensorMapFloatOOBfill);

static void encode2d(EncodeTiledFn enc, CUtensorMap* m, void* p, uint64_t cols, uint64_t rows, uint32_t bc, uint32_t br,
                     CUtensorMapSwizzle swz = CU_TENSOR_MAP_SWIZZLE_NONE) {
    cuuint64_t gd[2] = {cols, rows};
    cuuint64_t gs[1] = {cols * 2};
    cuuint32_t bx[2] = {bc, br};
    cuuint32_t es[2] = {1, 1};
    enc(m, CU_TENSOR_MAP_DATA_TYPE_BFLOAT16, 2, p, gd, gs, bx, es, CU_TENSOR_MAP_INTERLEAVE_NONE, swz,
        W_PROMO, CU_TENSOR_MAP_FLOAT_OOB_FILL_NONE);
}
static void encode_rows(EncodeTiledFn enc, CUtensorMap* m, void* p, uint64_t rows) {
    cuuint64_t gd[3] = {64, rows, 9};
    cuuint64_t gs[2] = {D_MODEL * 2, 128};
    cuuint32_t bx[3] = {64, 8, 9};
    cuuint32_t es[3] = {1, 1, 1};
    enc(m, CU_TENSOR_MAP_DATA_TYPE_BFLOAT16, 3, p, gd, gs, bx, es, CU_TENSOR_MAP_INTERLEAVE_NONE, CU_TENSOR_MAP_SWIZZLE_128B,
        CU_TENSOR_MAP_L2_PROMOTION_NONE, CU_TENSOR_MAP_FLOAT_OOB_FILL_NONE);
}
static void encode_kv(EncodeTiledFn enc, CUtensorMap* m, void* p) {
    cuuint64_t gd[3] = {64, (cuuint64_t)2 * HKV * SK, 2};
    cuuint64_t gs[2] = {256, 128};
    cuuint32_t bx[3] = {64, TILE_KEYS, 2};
    cuuint32_t es[3] = {1, 1, 1};
    enc(m, CU_TENSOR_MAP_DATA_TYPE_BFLOAT16, 3, p, gd, gs, bx, es, CU_TENSOR_MAP_INTERLEAVE_NONE, CU_TENSOR_MAP_SWIZZLE_128B,
        KV_PROMO, CU_TENSOR_MAP_FLOAT_OOB_FILL_NONE);
}

extern "C" void kernel_launch(void* const* d_in, const int* in_sizes, int n_in, void* d_out, int out_size) {
    (void)in_sizes; (void)n_in; (void)out_size;
    static EncodeTiledFn enc = nullptr;
    if (!enc) {
        cudaDriverEntryPointQueryResult qr;
        cudaGetDriverEntryPoint("cuTensorMapEncodeTiled", (void**)&enc, cudaEnableDefault, &qr);
        cudaFuncSetAttribute(fused_decode_kernel, cudaFuncAttributeMaxDynamicSharedMemorySize, SM_TOTAL);
    }
    CUtensorMap mk, mv, mwo, mw1, mw3, mw2, mwq;
    encode2d(enc, &mwq, d_in[3], QDIM, D_MODEL, 32, 144, CU_TENSOR_MAP_SWIZZLE_64B);
    encode_kv(enc, &mk, d_in[1]);
    encode_kv(enc, &mv, d_in[2]);
    encode_rows(enc, &mwo, d_in[4], QDIM);
    encode2d(enc, &mw1, d_in[6], FF, D_MODEL, 40, 72);
    encode2d(enc, &mw3, d_in[7], FF, D_MODEL, 40, 72);
    encode_rows(enc, &mw2, d_in[8], FF);
    cudaLaunchConfig_t cfg = {};
    cfg.gridDim = dim3(NCTA); cfg.blockDim = dim3(NTHREADS); cfg.dynamicSmemBytes = SM_TOTAL; cfg.stream = cudaStreamPerThread;
    cudaLaunchAttribute at[1];
    at[0].id = cudaLaunchAttributeCooperative; at[0].val.cooperative = 1;
    cfg.attrs = at; cfg.numAttrs = COOP;
    cudaLaunchKernelEx(&cfg, fused_decode_kernel, mk, mv, mwo, mw1, mw3, mw2, mwq, (const __nv_bfloat16*)d_in[0], (__nv_bfloat16*)d_out);
}
```

```cpp
#include <cuda_runtime.h>
#include <cuda_bf16.h>
#include <cuda.h>
#include <stdint.h>

namespace {

constexpr int D_MODEL = 576;
constexpr int HKV = 16;
constexpr int SK = 32768;
constexpr int QDIM = 4096;
constexpr int FF = 4608;

constexpr int NCTA = 128;
constexpr int NTHREADS = 384;
constexpr int TILE_KEYS = 64;
constexpr int NTILES = SK / 4 / TILE_KEYS;
constexpr int SLOT_BYTES = TILE_KEYS * 256;
constexpr int NSLOTS = 8;
constexpr int NKV = 2 * NTILES;
constexpr int NRED = 72;

constexpr int START_LOADS = 6, DEPTH_START = 2;
constexpr int DEPTH_MAIN = 4, DEPTH_MIN = 2;
constexpr int EARLY_W = 5;
constexpr int KV_LEFT = 2;
constexpr int DEPTH_WO = 6, DEPTH_W13 = 7, DEPTH_W2 = 5;
constexpr int SETUP_AT = 190;
constexpr int PROBES = 4;

constexpr int WQ_PIECE = 144 * 64;
constexpr int W13_PIECE = 72 * 80;
constexpr int ROW8_PIECE = 8 * 1152;

constexpr int SM_RING = 0;
constexpr int SM_WO = SM_RING;
constexpr int SM_W3B = SM_RING + 3 * SLOT_BYTES;
constexpr int SM_W2 = SM_RING + 4 * SLOT_BYTES;
constexpr int SM_W1 = NSLOTS * SLOT_BYTES;
constexpr int SM_BAR = SM_W1 + 14 * W13_PIECE;
constexpr int SM_RED = SM_BAR + 368;
constexpr int SM_XN = SM_RED + 4096;
constexpr int XN_PITCH = 584 * 2;
constexpr int SM_ML = SM_RED + 8 * 80 * 16;
constexpr int SM_Q = SM_ML + 64;
constexpr int SM_D1 = SM_Q + 512;
constexpr int SM_ACT = SM_D1 + 512;
constexpr int SM_RED4 = SM_ACT + 192;
constexpr int SM_HS = SM_RED4 + 512;
constexpr int SM_ONES = SM_HS + 8 * 18 * 16;
constexpr int SM_PROG = SM_ONES + 16;
constexpr int SM_HOME = SM_PROG + 16;
constexpr int SM_TOTAL = SM_HOME + 144;
static_assert(SM_TOTAL <= 232448, "smem");

constexpr unsigned SENTINEL = 0xFFFFFFFFu;
constexpr float LOG2E = 1.4426950408889634f;
constexpr float SCALE = 0.08838834764831845f;
constexpr unsigned SPIN_LIMIT = 1u << 24;

}

__device__ __align__(128) unsigned g_sync[3 * 32];
__device__ __align__(128) uint2 g_pq[2][HKV][128];
constexpr uint32_t X_P3 = 0, X_P1 = 8 * 8192, X_P2 = 72 * 8192, X_PR = 216 * 8192, X_END = 232 * 8192;
constexpr uint32_t P4_OFF = 16384;
__device__ __forceinline__ uint32_t p2_block(int rd) { return X_P2 + (rd >> 1) * 32768 + (rd & 1) * 8192; }
static_assert(X_END <= (2u << 20), "one page");
__device__ unsigned char g_xraw[(2u << 20) + X_END];
__device__ __align__(128) unsigned g_home[NCTA];
__device__ __forceinline__ uint32_t near_of(uint32_t blk, uint32_t side) { return blk + (((__popc(blk & 0xB2000u) ^ side) & 1) << 12); }

__device__ __forceinline__ void mbar_init(uint32_t bar, uint32_t cnt) {
    asm volatile("mbarrier.init.shared::cta.b64 [%0], %1;" ::"r"(bar), "r"(cnt) : "memory");
}
__device__ __forceinline__ void mbar_expect_tx(uint32_t bar, uint32_t bytes) {
    asm volatile("mbarrier.arrive.expect_tx.shared::cta.b64 _, [%0], %1;" ::"r"(bar), "r"(bytes) : "memory");
}
__device__ __forceinline__ void mbar_arrive(uint32_t bar) {
    asm volatile("mbarrier.arrive.shared::cta.b64 _, [%0];" ::"r"(bar) : "memory");
}
__device__ __forceinline__ void mbar_wait(uint32_t bar, uint32_t parity) {
    asm volatile("{\n.reg .pred p;\n.reg .u32 n;\nmov.u32 n, 0;\n"
                 "WAIT_LOOP:\nmbarrier.try_wait.parity.shared::cta.b64 p, [%0], %1;\n@p bra WAIT_DONE;\n"
                 "add.u32 n, n, 1;\nsetp.lt.u32 p, n, 0x1000000;\n@p bra WAIT_LOOP;\ntrap;\nWAIT_DONE:\n}"
                 ::"r"(bar), "r"(parity) : "memory");
}
__device__ __forceinline__ bool mbar_test(uint32_t bar, uint32_t parity) {
    uint32_t ok;
    asm volatile("{\n.reg .pred p;\nmbarrier.test_wait.parity.shared::cta.b64 p, [%1], %2;\nselp.u32 %0, 1, 0, p;\n}"
                 : "=r"(ok) : "r"(bar), "r"(parity) : "memory");
    return ok != 0;
}
__device__ __forceinline__ void mbar_wait_all(uint32_t bar) {
    uint32_t ok;
    unsigned n = 0;
    do {
        if (++n > SPIN_LIMIT) __trap();
        asm volatile("{\n.reg .pred p;\nmbarrier.try_wait.parity.shared::cta.b64 p, [%1], 0;\nselp.u32 %0, 1, 0, p;\n}"
                     : "=r"(ok) : "r"(bar) : "memory");
    } while (!__all_sync(0xffffffffu, ok));
    __syncwarp();
}
__device__ __forceinline__ void bar_sync(int id, int n) { asm volatile("bar.sync %0, %1;" ::"r"(id), "r"(n) : "memory"); }
__device__ __forceinline__ void bar_arrive(int id, int n) { asm volatile("bar.arrive %0, %1;" ::"r"(id), "r"(n) : "memory"); }

__device__ __forceinline__ void tma2d(uint32_t dst, const CUtensorMap* m, int c0, int c1, uint32_t bar) {
    asm volatile("cp.async.bulk.tensor.2d.shared::cluster.global.mbarrier::complete_tx::bytes [%0], [%1, {%3, %4}], [%2];"
                 ::"r"(dst), "l"(m), "r"(bar), "r"(c0), "r"(c1) : "memory");
}
__device__ __forceinline__ void tma3d(uint32_t dst, const CUtensorMap* m, int c1, uint32_t bar) {
    asm volatile("cp.async.bulk.tensor.3d.shared::cluster.global.mbarrier::complete_tx::bytes [%0], [%1, {0, %3, 0}], [%2];"
                 ::"r"(dst), "l"(m), "r"(bar), "r"(c1) : "memory");
}
__device__ __forceinline__ void tma3d_hint(uint32_t dst, const CUtensorMap* m, int c1, uint32_t bar, uint64_t pol) {
    asm volatile("cp.async.bulk.tensor.3d.shared::cluster.global.mbarrier::complete_tx::bytes.L2::cache_hint [%0], [%1, {0, %3, 0}], [%2], %4;"
                 ::"r"(dst), "l"(m), "r"(bar), "r"(c1), "l"(pol) : "memory");
}
__device__ __forceinline__ void ldsm4(uint32_t (&r)[4], uint32_t a) {
    asm volatile("ldmatrix.sync.aligned.m8n8.x4.shared.b16 {%0,%1,%2,%3}, [%4];"
                 : "=r"(r[0]), "=r"(r[1]), "=r"(r[2]), "=r"(r[3]) : "r"(a) : "memory");
}
__device__ __forceinline__ void ldsm4t(uint32_t (&r)[4], uint32_t a) {
    asm volatile("ldmatrix.sync.aligned.m8n8.x4.trans.shared.b16 {%0,%1,%2,%3}, [%4];"
                 : "=r"(r[0]), "=r"(r[1]), "=r"(r[2]), "=r"(r[3]) : "r"(a) : "memory");
}
__device__ __forceinline__ void ldsm2t(uint32_t& r0, uint32_t& r1, uint32_t a) {
    asm volatile("ldmatrix.sync.aligned.m8n8.x2.trans.shared.b16 {%0,%1}, [%2];" : "=r"(r0), "=r"(r1) : "r"(a) : "memory");
}
__device__ __forceinline__ void ldsm1(uint32_t& r0, uint32_t a) {
    asm volatile("ldmatrix.sync.aligned.m8n8.x1.shared.b16 {%0}, [%1];" : "=r"(r0) : "r"(a) : "memory");
}
__device__ __forceinline__ void mma16816(float (&c)[4], uint32_t a0, uint32_t a1, uint32_t a2, uint32_t a3, uint32_t b0, uint32_t b1) {
    asm("mma.sync.aligned.m16n8k16.row.col.f32.bf16.bf16.f32 {%0,%1,%2,%3}, {%4,%5,%6,%7}, {%8,%9}, {%0,%1,%2,%3};"
                 : "+f"(c[0]), "+f"(c[1]), "+f"(c[2]), "+f"(c[3]) : "r"(a0), "r"(a1), "r"(a2), "r"(a3), "r"(b0), "r"(b1));
}
__device__ __forceinline__ float4 lds128(uint32_t a) {
    float4 v;
    asm volatile("ld.shared.v4.f32 {%0,%1,%2,%3}, [%4];" : "=f"(v.x), "=f"(v.y), "=f"(v.z), "=f"(v.w) : "r"(a) : "memory");
    return v;
}
__device__ __forceinline__ void sts64(uint32_t a, float x, float y) {
    asm volatile("st.shared.v2.f32 [%0], {%1,%2};" ::"r"(a), "f"(x), "f"(y) : "memory");
}
__device__ __forceinline__ void mma1688(float (&c)[4], uint32_t a0, uint32_t a1, uint32_t b0) {
    asm("mma.sync.aligned.m16n8k8.row.col.f32.bf16.bf16.f32 {%0,%1,%2,%3}, {%4,%5}, {%6}, {%0,%1,%2,%3};"
                 : "+f"(c[0]), "+f"(c[1]), "+f"(c[2]), "+f"(c[3]) : "r"(a0), "r"(a1), "r"(b0));
}
__device__ __forceinline__ uint32_t movm(uint32_t a) {
    uint32_t d;
    asm volatile("movmatrix.sync.aligned.m8n8.trans.b16 %0, %1;" : "=r"(d) : "r"(a));
    return d;
}
__device__ __forceinline__ uint32_t pack_bf16(float lo, float hi) {
    uint32_t d;
    asm("cvt.rn.bf16x2.f32 %0, %1, %2;" : "=r"(d) : "f"(hi), "f"(lo));
    return d;
}
__device__ __forceinline__ float bf_lo(uint32_t v) { return __uint_as_float(v << 16); }
__device__ __forceinline__ float bf_hi(uint32_t v) { return __uint_as_float(v & 0xFFFF0000u); }
__device__ __forceinline__ float bfr(float x) { return __uint_as_float(pack_bf16(0.f, x)); }
__device__ __forceinline__ float ex2(float x) { float y; asm("ex2.approx.ftz.f32 %0, %1;" : "=f"(y) : "f"(x)); return y; }
__device__ __forceinline__ float rcp(float x) { float y; asm("rcp.approx.ftz.f32 %0, %1;" : "=f"(y) : "f"(x)); return y; }

__device__ __forceinline__ void ld_relaxed128_if(uint4& v, const void* p, bool need) {
    asm volatile("{\n.reg .pred q;\n.reg .b128 t;\n.reg .b64 lo, hi;\nsetp.ne.u32 q, %5, 0;\nmov.b64 lo, {%0, %1};\nmov.b64 hi, {%2, %3};\n"
                 "mov.b128 t, {lo, hi};\n@q ld.relaxed.gpu.global.b128 t, [%4];\nmov.b128 {lo, hi}, t;\n"
                 "mov.b64 {%0, %1}, lo;\nmov.b64 {%2, %3}, hi;\n}"
                 : "+r"(v.x), "+r"(v.y), "+r"(v.z), "+r"(v.w) : "l"(p), "r"((unsigned)need) : "memory");
}
__device__ __forceinline__ void st_relaxed128(void* p, uint32_t x, uint32_t y, uint32_t z, uint32_t w) {
    asm volatile("{\n.reg .b128 t;\n.reg .b64 lo, hi;\nmov.b64 lo, {%1, %2};\nmov.b64 hi, {%3, %4};\nmov.b128 t, {lo, hi};\n"
                 "st.relaxed.gpu.global.b128 [%0], t;\n}"
                 ::"l"(p), "r"(x), "r"(y), "r"(z), "r"(w) : "memory");
}
__device__ __forceinline__ uint2 ld_relaxed64(const void* p) {
    uint2 v;
    asm volatile("{\n.reg .b64 t;\nld.relaxed.gpu.global.b64 t, [%2];\nmov.b64 {%0, %1}, t;\n}" : "=r"(v.x), "=r"(v.y) : "l"(p) : "memory");
    return v;
}
__device__ __forceinline__ void st_relaxed64(void* p, uint32_t x, uint32_t y) {
    asm volatile("{\n.reg .b64 t;\nmov.b64 t, {%1, %2};\nst.relaxed.gpu.global.b64 [%0], t;\n}" ::"l"(p), "r"(x), "r"(y) : "memory");
}
__device__ __forceinline__ unsigned ld_relaxed32(const void* p) {
    unsigned v;
    asm volatile("ld.relaxed.gpu.global.u32 %0, [%1];" : "=r"(v) : "l"(p) : "memory");
    return v;
}
__device__ __forceinline__ void st_relaxed32(void* p, unsigned v) {
    asm volatile("st.relaxed.gpu.global.u32 [%0], %1;" ::"l"(p), "r"(v) : "memory");
}
__device__ __forceinline__ void red_add(unsigned* p) {
    asm volatile("red.relaxed.gpu.global.add.u32 [%0], 1;" ::"l"(p) : "memory");
}
__device__ __forceinline__ bool valid4(const uint4& v) {
    return v.x != SENTINEL && v.y != SENTINEL && v.z != SENTINEL && v.w != SENTINEL;
}

__device__ __forceinline__ unsigned near_page(unsigned* p) {
#pragma unroll
    for (int i = 0; i < 4; i++) st_relaxed128(p + (i >> 1) * 1024 + (i & 1) * 4, 0, 0, 0, 0);
    unsigned best0 = 0xffffffffu, best1 = 0xffffffffu;
#pragma unroll 1
    for (int i = 0; i < 2 * PROBES + 1; i++) {
        unsigned v, t0, t1;
        asm volatile("mov.u32 %0, %%clock;" : "=r"(t0) :: "memory");
        asm volatile("atom.relaxed.gpu.global.add.u32 %0, [%1], 1;" : "=r"(v) : "l"(p + ((i & 1) << 10)) : "memory");
        asm volatile("{\n.reg .pred p;\nsetp.ne.u32 p, %1, 0x5a5a5a5a;\nmov.u32 %0, 0;\n@p mov.u32 %0, %%clock;\n}" : "=r"(t1) : "r"(v) : "memory");
        if (i & 1) best1 = min(best1, t1 - t0); else best0 = min(best0, t1 - t0);
    }
    return best1 < best0;
}

__device__ __forceinline__ uint32_t finish_sum(uint32_t a, uint32_t res) {
    float2 c[8];
#pragma unroll
    for (int i = 0; i < 8; i++) asm volatile("ld.shared.v2.f32 {%0,%1}, [%2];" : "=f"(c[i].x), "=f"(c[i].y) : "r"(a + i * 64) : "memory");
    const uint32_t t = pack_bf16(((c[0].x + c[1].x) + (c[2].x + c[3].x)) + ((c[4].x + c[5].x) + (c[6].x + c[7].x)),
                                 ((c[0].y + c[1].y) + (c[2].y + c[3].y)) + ((c[4].y + c[5].y) + (c[6].y + c[7].y)));
    return pack_bf16(bf_lo(res) + bf_lo(t), bf_hi(res) + bf_hi(t));
}

enum { BAR_ALL = 1, BAR_MAIN = 2, BAR_HELP = 3, BAR_RDY = 4, BAR_INIT = 5, BAR_PROBE = 6, BAR_F1 = 7, BAR_VEC = 8,
       BAR_SUM = 9, BAR_OWN = 10, BAR_H = 11, BAR_P2 = 12, BAR_AUX = 13 };
#define PIN(v) asm volatile("" : "+r"(v))

__global__ void __launch_bounds__(NTHREADS, 1)
fused_decode_kernel(const __grid_constant__ CUtensorMap map_k, const __grid_constant__ CUtensorMap map_v,
                    const __grid_constant__ CUtensorMap map_wo, const __grid_constant__ CUtensorMap map_w1,
                    const __grid_constant__ CUtensorMap map_w3, const __grid_constant__ CUtensorMap map_w2,
                    const __grid_constant__ CUtensorMap map_wq, const __nv_bfloat16* __restrict__ x,
                    __nv_bfloat16* __restrict__ out) {
    extern __shared__ __align__(1024) unsigned char smem[];
    const uint32_t sb = (uint32_t)__cvta_generic_to_shared(smem);
    const int tid = threadIdx.x, lane = tid & 31;
    if (tid == 0) {
        const uint32_t bw = sb + SM_BAR + 128;
#pragma unroll
        for (int p = 0; p < 4; p++) mbar_init(bw + 8 * p, 1);
#pragma unroll
        for (int p = 0; p < 4; p++) {
            mbar_expect_tx(bw + 8 * p, WQ_PIECE);
            tma2d(sb + SM_W1 + p * WQ_PIECE, &map_wq, blockIdx.x * 32, p * 144, bw + 8 * p);
        }
    }
    if (tid < 32) { __syncwarp(); bar_arrive(BAR_INIT, 96); }
    const int warp = __shfl_sync(0xffffffffu, tid >> 5, 0);
    const int cta = blockIdx.x;
    const int hkv = cta >> 3, r = cta & 7;
    const uint32_t bar_full = sb + SM_BAR, bar_empty = bar_full + 64, bar_w = bar_full + 128,
                   bar_l = bar_full + 160;
    volatile int* const prog = reinterpret_cast<volatile int*>(smem + SM_PROG);
    float* const red = reinterpret_cast<float*>(smem + SM_RED);
    unsigned char* const g_x = reinterpret_cast<unsigned char*>((reinterpret_cast<uintptr_t>(g_xraw) + 0x1FFFFF) & ~(uintptr_t)0x1FFFFF);
    const int g = lane >> 2, t4 = lane & 3;

    if (warp == 8) {
        bar_sync(BAR_INIT, 96);
        const int f0 = (cta >> 1) * 72 + (cta & 1) * 32;
        const int early = EARLY_W + 1 - (cta & 1);
        if (lane == 0) {
            uint64_t pol;
            asm volatile("createpolicy.fractional.L2::evict_first.b64 %0, 1.0;" : "=l"(pol));
            const int row0 = ((r >> 2) * HKV + hkv) * SK + (r & 3) * (2 * TILE_KEYS);
#pragma unroll 1
            for (int i = 0; i < NKV; i++) {
                const int slot = i & (NSLOTS - 1);
                if (i >= NSLOTS) mbar_wait(bar_empty + 8 * slot, ((i >> 3) - 1) & 1);
                const int j = i - (i < START_LOADS ? DEPTH_START : (int)prog[1]);
                if (j >= 0) mbar_wait(bar_full + 8 * (j & 7), (j >> 3) & 1);
                else if (i == 1) mbar_wait(bar_w + 8, 0);
                prog[0] = j + 1;
                const int row = row0 + (i >> 2) * (8 * TILE_KEYS) + ((i >> 1) & 1) * TILE_KEYS;
                mbar_expect_tx(bar_full + 8 * slot, SLOT_BYTES);
                tma3d_hint(sb + SM_RING + slot * SLOT_BYTES, (i & 1) ? &map_v : &map_k, row, bar_full + 8 * slot, pol);
                if (i >= 32 && i < 32 + early) {
                    mbar_expect_tx(bar_l + 32 + 8 * slot, W13_PIECE);
                    tma2d(sb + SM_W1 + slot * W13_PIECE, &map_w1, f0, slot * 72, bar_l + 32 + 8 * slot);
                }
                if (i == NKV - 32) {
                    asm volatile("prefetch.tensormap [%0];" ::"l"(&map_wo) : "memory");
                    asm volatile("prefetch.tensormap [%0];" ::"l"(&map_w3) : "memory");
                    asm volatile("prefetch.tensormap [%0];" ::"l"(&map_w2) : "memory");
                }
            }
            prog[0] = NKV;
        }
        __syncwarp();
        {
            const int q = lane, p = q < 4 ? q : q + early;
            const bool rows = p < 4 || p >= 20;
            const uint32_t bar = bar_l + 8 * p;
            const CUtensorMap* map = p < 4 ? &map_wo : p < 12 ? &map_w1 : p < 20 ? &map_w3 : &map_w2;
            const uint32_t dst = sb + (p < 4 ? SM_WO + p * ROW8_PIECE : p < 18 ? SM_W1 + (p - 4) * W13_PIECE
                                     : p < 20 ? SM_W3B + (p - 18) * W13_PIECE : SM_W2 + (p - 20) * ROW8_PIECE);
            const int row = p < 4 ? cta * 32 + p * 8 : p < 20 ? ((p - 4) & 7) * 72 : f0 + (p - 20) * 8;
            const int d = q < 6 ? DEPTH_WO : p < 20 ? DEPTH_W13 : max(DEPTH_W2, DEPTH_W13 + 19 - p);
            const int qa = q - d;
            const uint32_t ga = qa >= 0 ? bar_l + 8 * (qa < 4 ? qa : qa + early) : bar_full + 8 * min(7, 7 - KV_LEFT + (q >> 1));
            const uint32_t gb = bar_empty + 8 * (p >= 20 ? 6 : 3);
            bool todo = p < 25;
            if (p == 20 && (cta & 1)) {
                mbar_arrive(bar);
                todo = false;
            }
            if (todo) mbar_expect_tx(bar, rows ? ROW8_PIECE : W13_PIECE);
            unsigned n = 0;
            while (__any_sync(0xffffffffu, todo)) {
                if (++n > (SPIN_LIMIT << 2)) __trap();
                if (todo && (prog[2] || mbar_test(ga, qa >= 0 ? 0 : 1)) && mbar_test(gb, 1)) {
                    if (rows) tma3d(dst, map, row, bar); else tma2d(dst, map, f0, row, bar);
                    todo = false;
                }
            }
        }
        return;
    }

    if (warp > 8) {
        if (warp == 9) {
            if (lane == 0) {
#pragma unroll 1
                for (int i = 0; i < 8; i++) { mbar_init(bar_full + 8 * i, 1); mbar_init(bar_empty + 8 * i, 4); }
                prog[0] = 0; prog[1] = DEPTH_MAIN; prog[2] = 0;
#pragma unroll 5
                for (int i = 0; i < 25; i++) mbar_init(bar_l + 8 * i, 1);
                *reinterpret_cast<uint4*>(smem + SM_ONES) = make_uint4(0x3F803F80u, 0x3F803F80u, 0x3F803F80u, 0x3F803F80u);
            }
            __syncwarp();
            bar_arrive(BAR_INIT, 96);
            bar_arrive(0, 288);
        }
        if (lane == 0) {
            const uint32_t blk = X_PR + (cta & 15) * 8192;
            smem[SM_HOME + 128 + warp - 9] = (near_page(reinterpret_cast<unsigned*>(g_x + blk + (cta >> 4) * 512 + (warp - 9) * 128)) ^ __popc(blk & 0xB2000u)) & 1;
        }
        __syncwarp();
        bar_sync(BAR_PROBE, 224);
        uint32_t res = 0, rs4 = sb + SM_RED4 + (lane & 7) * 8;
        const unsigned side = (smem[SM_HOME + 128] + smem[SM_HOME + 129] + smem[SM_HOME + 130]) >> 1;
        if (warp == 9) {
            if (lane == 0) {
                int last = 0, cur;
                unsigned n = 0;
                do {
                    if (++n > SPIN_LIMIT) __trap();
                    __nanosleep(1000);
                    cur = prog[0];
                    const int tot = (int)atomicAdd(&g_sync[64], (unsigned)(cur - last));
                    last = cur;
                    const int lead = prog[(unsigned)tot >> 31] * NCTA - tot;
                    prog[1] = max(DEPTH_MIN, min(NSLOTS, DEPTH_MAIN + (((cur < NKV - 12 ? 63 : 191) - lead) >> 8)));
                } while (cur < NKV - 8);
            }
            __syncwarp();
        } else if (warp == 10) {
            const unsigned char* pp = g_x + near_of(X_P1 + (cta >> 1) * 8192, side) + (cta & 1) * 2048 + (lane >> 4) * 1024 + (lane & 15) * 16;
            uint32_t oa = sb + SM_ACT + (lane >> 4) * 80 + 16 + (lane & 15) * 4;
            PIN(oa);
            uint4 v[4];
#pragma unroll
            for (int i = 0; i < 4; i++) v[i] = make_uint4(0, 0, 0, SENTINEL);
            unsigned n = 0;
            bar_sync(BAR_OWN, 160);
            do {
                if (++n > SPIN_LIMIT) __trap();
#pragma unroll
                for (int i = 0; i < 4; i++) ld_relaxed128_if(v[i], pp + i * 256, v[i].w == SENTINEL);
            } while (__any_sync(0xffffffffu, v[0].w == SENTINEL || v[1].w == SENTINEL || v[2].w == SENTINEL || v[3].w == SENTINEL));
            const float W = fmaxf(fmaxf(__uint_as_float(v[0].z), __uint_as_float(v[1].z)), fmaxf(__uint_as_float(v[2].z), __uint_as_float(v[3].z)));
            float e[4];
#pragma unroll
            for (int i = 0; i < 4; i++) e[i] = ex2((__uint_as_float(v[i].z) - W) * LOG2E);
            const float inv = rcp(fmaf(e[0], __uint_as_float(v[0].w), e[1] * __uint_as_float(v[1].w)) + fmaf(e[2], __uint_as_float(v[2].w), e[3] * __uint_as_float(v[3].w)));
            const float o0 = fmaf(e[0], __uint_as_float(v[0].x), e[1] * __uint_as_float(v[1].x)) + fmaf(e[2], __uint_as_float(v[2].x), e[3] * __uint_as_float(v[3].x));
            const float o1 = fmaf(e[0], __uint_as_float(v[0].y), e[1] * __uint_as_float(v[1].y)) + fmaf(e[2], __uint_as_float(v[2].y), e[3] * __uint_as_float(v[3].y));
            asm volatile("st.shared.u32 [%0], %1;" ::"r"(oa), "r"(pack_bf16(o0 * inv, o1 * inv)) : "memory");
            __syncwarp();
            bar_arrive(BAR_VEC, 288);
        } else if (cta < NRED) {
            res = ld_relaxed32(reinterpret_cast<const uint32_t*>(x + (g & 1) * D_MODEL + cta * 8) + t4);
            unsigned char* hp = g_x + X_P3 + (lane >> 3) * 16384 + cta * 32 + (lane & 7) * 4;
            PIN(res); PIN(rs4);
            bar_sync(BAR_SUM, 288);
            res = finish_sum(rs4, res);
#pragma unroll
            for (int i = 0; i < 4; i++) st_relaxed32(hp + i * 4096, res);
        }
        if (warp < 11) {
            const uint32_t off = ((warp - 9) * 72 + lane) * 16;
            const unsigned char* hp = g_x + near_of(X_P3 + (cta & 7) * 8192, side) + off;
            uint4 u[3];
            bool need[3];
#pragma unroll
            for (int i = 0; i < 3; i++) { u[i] = make_uint4(0, 0, 0, 0); need[i] = lane < 24; }
            bar_sync(BAR_P2, 352);
            unsigned n = 0;
            do {
                if (++n > SPIN_LIMIT) __trap();
#pragma unroll
                for (int i = 0; i < 3; i++) ld_relaxed128_if(u[i], hp + i * 384, need[i]);
#pragma unroll
                for (int i = 0; i < 3; i++) need[i] = !valid4(u[i]);
                if (lane < 24 && !(need[0] && need[1] && need[2])) prog[2] = 1;
            } while (__any_sync(0xffffffffu, need[0] || need[1] || need[2]));
            if (lane < 24) {
#pragma unroll
                for (int i = 0; i < 3; i++) *reinterpret_cast<uint4*>(smem + SM_HS + off + i * 384) = u[i];
            }
            __syncwarp();
            bar_arrive(BAR_H, 320);
            float sm = 0.f, sq = 0.f;
#pragma unroll
            for (int i = 0; i < 3; i++) {
                const uint32_t w[4] = {u[i].x, u[i].y, u[i].z, u[i].w};
                float s1 = 0.f, s2 = 0.f;
#pragma unroll
                for (int k = 0; k < 4; k++) {
                    const float lo = bf_lo(w[k]), hi = bf_hi(w[k]);
                    s1 += lo + hi;
                    s2 = fmaf(lo, lo, fmaf(hi, hi, s2));
                }
                sm += s1; sq += s2;
            }
#pragma unroll
            for (int o = 2; o < 32; o <<= 1) {
                sm += __shfl_xor_sync(0xffffffffu, sm, o);
                sq += __shfl_xor_sync(0xffffffffu, sq, o);
            }
            if (lane < 2) *reinterpret_cast<float2*>(smem + SM_ML + lane * 16 + (warp - 9) * 8) = make_float2(sm, sq);
        } else {
            bar_arrive(BAR_P2, 352);
        }
        bar_sync(BAR_AUX, 96);
        const int at = tid - 288, bb = at & 1;
        uint32_t ra = sb + SM_RED + min(at, 79) * 16;
        uint32_t wa = sb + SM_ACT + bb * 80 + (at >> 1) * 2;
        const float4 st = lds128(sb + SM_ML + bb * 16);
        const float mean = (st.x + st.z) * (1.f / D_MODEL);
        const float var = fmaxf(fmaf(-mean, mean, (st.y + st.w) * (1.f / D_MODEL)), 0.f);
        float mb = bfr(mean), sd, isd;
        asm("sqrt.approx.ftz.f32 %0, %1;" : "=f"(sd) : "f"(bfr(bfr(var) + 1e-5f)));
        asm volatile("rcp.approx.ftz.f32 %0, %1;" : "=f"(isd) : "f"(bfr(sd)));
        bar_sync(BAR_F1, 352);
        float4 u[8];
#pragma unroll
        for (int wv = 0; wv < 8; wv++) u[wv] = lds128(ra + wv * 80 * 16);
#pragma unroll
        for (int d = 4; d; d >>= 1) {
#pragma unroll
            for (int i = 0; i < d; i++) { u[i].x += u[i + d].x; u[i].y += u[i + d].y; u[i].z += u[i + d].z; }
        }
        const float v0 = u[0].x, v1 = u[0].y, cs = u[0].z;
        const float ov = __shfl_xor_sync(0xffffffffu, bb ? v0 : v1, 1), ocs = __shfl_xor_sync(0xffffffffu, cs, 1);
        const float gt = bfr(fmaf(-mb, bb ? ocs : cs, bb ? ov : v0) * isd);
        const float up = bfr(fmaf(-mb, bb ? cs : ocs, bb ? v1 : ov) * isd);
        const float act = bfr(gt * rcp(1.f + ex2(-gt * LOG2E))) * up;
        if (at < 80) asm volatile("st.shared.u16 [%0], %1;" ::"r"(wa), "h"((unsigned short)pack_bf16(act, 0.f)) : "memory");
        bar_arrive(BAR_VEC, 352);
        if (warp == 11 && cta < NRED) {
            uint32_t* op = reinterpret_cast<uint32_t*>(out + (g & 1) * D_MODEL + cta * 8) + t4;
            bar_sync(BAR_SUM, 288);
            res = finish_sum(rs4, res);
            if (lane < 8) *op = res;
            if (cta == 0 && lane == 0) {
                red_add(&g_sync[0]);
                st_relaxed32(&g_sync[32], 0);
                st_relaxed32(&g_sync[64], 0);
            }
        }
        return;
    }

    unsigned tag;
    {
        const uint32_t* xp = reinterpret_cast<const uint32_t*>(x + (warp >> 2) * D_MODEL);
        uint32_t xu[9], xo[3];
#pragma unroll
        for (int i = 0; i < 9; i++) xu[i] = __ldg(xp + lane + 32 * i);
        tag = ld_relaxed32(&g_sync[0]) + 1;
        const int wq4 = warp & 3;
        xo[0] = wq4 == 0 ? xu[0] : wq4 == 1 ? xu[1] : wq4 == 2 ? xu[2] : xu[3];
        xo[1] = wq4 == 0 ? xu[4] : wq4 == 1 ? xu[5] : wq4 == 2 ? xu[6] : xu[7];
        xo[2] = xu[8];
        float s = 0.f;
#pragma unroll
        for (int i = 0; i < 9; i++) s += bf_lo(xu[i]) + bf_hi(xu[i]);
#pragma unroll
        for (int o = 16; o; o >>= 1) s += __shfl_xor_sync(0xffffffffu, s, o);
        const float mean = __fdiv_rn(s, (float)D_MODEL);
        float q2 = 0.f;
#pragma unroll
        for (int i = 0; i < 9; i++) {
            const float d0 = bf_lo(xu[i]) - mean, d1 = bf_hi(xu[i]) - mean;
            q2 = fmaf(d0, d0, fmaf(d1, d1, q2));
        }
#pragma unroll
        for (int o = 16; o; o >>= 1) q2 += __shfl_xor_sync(0xffffffffu, q2, o);
        const float mb = bfr(mean);
        const float sd = bfr(__fsqrt_rn(bfr(bfr(__fdiv_rn(q2, (float)D_MODEL)) + 1e-5f)));
#pragma unroll 1
        for (int i = 0; i < 3; i++) {
            const uint32_t u = i == 0 ? xo[0] : i == 1 ? xo[1] : xo[2];
            const int wi = i < 2 ? 4 * i + wq4 : 8;
            *reinterpret_cast<uint32_t*>(smem + SM_XN + (warp >> 2) * XN_PITCH + 4 * (lane + 32 * wi)) =
                pack_bf16(__fdiv_rn(bfr(bf_lo(u) - mb), sd), __fdiv_rn(bfr(bf_hi(u) - mb), sd));
        }
        bar_sync(0, 288);
        uint32_t xb[12];
        const uint32_t xa = sb + SM_XN + (lane & 1) * XN_PITCH + (warp * 72 + 8 * (lane >> 3)) * 2;
        ldsm4(*reinterpret_cast<uint32_t(*)[4]>(&xb[0]), xa);
        ldsm4(*reinterpret_cast<uint32_t(*)[4]>(&xb[4]), xa + 64);
        ldsm1(xb[8], xa + 128);
        mbar_wait(bar_w + 8 * (warp >> 1), 0);
        const uint32_t wa = sb + SM_W1 + (warp * 72 + (lane & 7) + 8 * (lane >> 4)) * 64;
        float qa[2][4];
#pragma unroll
        for (int j = 0; j < 2; j++) {
            const uint32_t ad = wa + (((2 * j + ((lane >> 3) & 1)) ^ ((lane >> 1) & 3)) << 4);
            qa[j][0] = qa[j][1] = qa[j][2] = qa[j][3] = 0.f;
#pragma unroll
            for (int ks = 0; ks < 4; ks++) {
                uint32_t a4[4];
                ldsm4t(a4, ad + ks * 16 * 64);
                mma16816(qa[j], a4[0], a4[1], a4[2], a4[3], xb[2 * ks], xb[2 * ks + 1]);
            }
            uint32_t a0, a1;
            ldsm2t(a0, a1, ad + 64 * 64);
            mma1688(qa[j], a0, a1, xb[8]);
        }
#pragma unroll
        for (int j = 0; j < 2; j++) {
            const float lo = (t4 & 1) ? qa[j][1] : qa[j][0], hi = (t4 & 1) ? qa[j][3] : qa[j][2];
            red[warp * 64 + (t4 & 1) * 32 + 16 * j + g + 8 * (t4 >> 1)] = (t4 & 2) ? hi : lo;
        }
        bar_sync(BAR_ALL, 256);
        if (warp == 0) {
            float s0 = 0.f, s1 = 0.f;
#pragma unroll
            for (int wv = 0; wv < 8; wv++) {
                const float2 v = *reinterpret_cast<const float2*>(red + wv * 64 + lane * 2);
                s0 += v.x; s1 += v.y;
            }
            st_relaxed64(&g_pq[lane >> 4][hkv][r * 16 + (lane & 15)], pack_bf16(s0, s1), tag);
        }
    }

    if (warp < 4) {
        float* const ml = reinterpret_cast<float*>(smem + SM_ML);
        uint32_t* const qs = reinterpret_cast<uint32_t*>(smem + SM_Q);
        {
            uint2 v;
            unsigned n = 0;
            do {
                if (++n > SPIN_LIMIT) __trap();
                __nanosleep(800);
                v = ld_relaxed64(&g_pq[r >> 2][hkv][tid]);
            } while (__any_sync(0xffffffffu, v.y != tag));
            qs[tid] = v.x;
            bar_sync(BAR_MAIN, 128);
        }
        uint32_t koff[4], voff[4];
        {
            const int l7 = lane & 7;
            const uint32_t kb = (warp * 16 + l7 + 8 * ((lane >> 3) & 1)) * 128;
            const uint32_t vb = (warp * 16 + l7 + 8 * (lane >> 4)) * 128;
#pragma unroll
            for (int i = 0; i < 4; i++) {
                koff[i] = sb + SM_RING + kb + (((2 * i + (lane >> 4)) ^ l7) << 4);
                voff[i] = sb + SM_RING + SLOT_BYTES + vb + (((2 * i + ((lane >> 3) & 1)) ^ l7) << 4);
            }
        }
        {
            uint32_t qb[8][2];
#pragma unroll
            for (int ks = 0; ks < 8; ks++) {
                qb[ks][0] = qs[(g & 1) * 64 + ks * 8 + t4];
                qb[ks][1] = qs[(g & 1) * 64 + ks * 8 + 4 + t4];
            }
            float o[8][4];
#pragma unroll
            for (int i = 0; i < 8; i++) { o[i][0] = o[i][1] = o[i][2] = o[i][3] = 0.f; }
            float m0 = -INFINITY, m1 = -INFINITY, l0 = 0.f, l1 = 0.f;
#pragma unroll 1
            for (int t = 0; t < NTILES; t++) {
                const int slot = (2 * t) & (NSLOTS - 1);
                const uint32_t ph = (t >> 2) & 1;
                const uint32_t so = slot * SLOT_BYTES;
                mbar_wait(bar_full + 8 * slot, ph);
                uint32_t a[8][4];
#pragma unroll
                for (int ks = 0; ks < 8; ks++) ldsm4(a[ks], koff[ks & 3] + so + (ks >> 2) * 8192);
                __syncwarp();
                if (lane == 0) mbar_arrive(bar_empty + 8 * slot);
                float c[4] = {0.f, 0.f, 0.f, 0.f}, c2[4] = {0.f, 0.f, 0.f, 0.f};
#pragma unroll
                for (int ks = 0; ks < 8; ks += 2) {
                    mma16816(c, a[ks][0], a[ks][1], a[ks][2], a[ks][3], qb[ks][0], qb[ks][1]);
                    mma16816(c2, a[ks + 1][0], a[ks + 1][1], a[ks + 1][2], a[ks + 1][3], qb[ks + 1][0], qb[ks + 1][1]);
                }
                uint32_t u0 = pack_bf16(c[0] + c2[0], c[1] + c2[1]), u1 = pack_bf16(c[2] + c2[2], c[3] + c2[3]);
                u0 = pack_bf16(bf_lo(u0) * SCALE, bf_hi(u0) * SCALE);
                u1 = pack_bf16(bf_lo(u1) * SCALE, bf_hi(u1) * SCALE);
                const float s0 = bf_lo(u0), s1 = bf_hi(u0), s2 = bf_lo(u1), s3 = bf_hi(u1);
                float x0 = fmaxf(s0, s2), x1 = fmaxf(s1, s3);
                if (__any_sync(0xffffffffu, x0 > m0 || x1 > m1)) {
#pragma unroll
                    for (int of = 4; of < 32; of <<= 1) {
                        x0 = fmaxf(x0, __shfl_xor_sync(0xffffffffu, x0, of));
                        x1 = fmaxf(x1, __shfl_xor_sync(0xffffffffu, x1, of));
                    }
                    x0 = fmaxf(m0, x0); x1 = fmaxf(m1, x1);
                    const float al0 = ex2((m0 - x0) * LOG2E), al1 = ex2((m1 - x1) * LOG2E);
                    m0 = x0; m1 = x1;
                    l0 *= al0; l1 *= al1;
#pragma unroll
                    for (int i = 0; i < 8; i++) { o[i][0] *= al0; o[i][1] *= al1; o[i][2] *= al0; o[i][3] *= al1; }
                }
                const float p0 = ex2((s0 - m0) * LOG2E), p1 = ex2((s1 - m1) * LOG2E);
                const float p2 = ex2((s2 - m0) * LOG2E), p3 = ex2((s3 - m1) * LOG2E);
                l0 += p0 + p2; l1 += p1 + p3;
                const uint32_t pb0 = movm(pack_bf16(p0, p1)), pb1 = movm(pack_bf16(p2, p3));
                mbar_wait(bar_full + 8 * slot + 8, ph);
#pragma unroll
                for (int mt = 0; mt < 8; mt++) ldsm4t(a[mt], voff[mt & 3] + so + (mt >> 2) * 8192);
                __syncwarp();
                if (lane == 0) mbar_arrive(bar_empty + 8 * slot + 8);
#pragma unroll
                for (int mt = 0; mt < 8; mt++) mma16816(o[mt], a[mt][0], a[mt][1], a[mt][2], a[mt][3], pb0, pb1);
            }
#pragma unroll
            for (int of = 4; of < 32; of <<= 1) {
                l0 += __shfl_xor_sync(0xffffffffu, l0, of);
                l1 += __shfl_xor_sync(0xffffffffu, l1, of);
            }
            if (lane < 2) *reinterpret_cast<float2*>(ml + lane * 8 + warp * 2) = lane ? make_float2(m1, l1) : make_float2(m0, l0);
            {
                float* dst = red + warp * 288 + (t4 & 1) * 144 + g + 8 * (t4 >> 1);
#pragma unroll
                for (int mt = 0; mt < 8; mt++) {
                    const float lo = (t4 & 1) ? o[mt][1] : o[mt][0], hi = (t4 & 1) ? o[mt][3] : o[mt][2];
                    dst[16 * mt] = (t4 & 2) ? hi : lo;
                }
            }
            bar_sync(BAR_RDY, 256);
            bar_arrive(BAR_OWN, 160);
            {
                const int h = tid >> 6, j = tid & 63;
                const float4 w01 = *reinterpret_cast<const float4*>(ml + h * 8), w23 = *reinterpret_cast<const float4*>(ml + h * 8 + 4);
                const float* op = red + h * 144 + 2 * j;
                const float2 v0 = *reinterpret_cast<const float2*>(op), v1 = *reinterpret_cast<const float2*>(op + 288);
                const float2 v2 = *reinterpret_cast<const float2*>(op + 576), v3 = *reinterpret_cast<const float2*>(op + 864);
                const uint32_t dst1 = reinterpret_cast<const uint32_t*>(smem + SM_D1)[tid];
                const float M = fmaxf(fmaxf(w01.x, w01.z), fmaxf(w23.x, w23.z));
                const float e0 = ex2((w01.x - M) * LOG2E), e1 = ex2((w01.z - M) * LOG2E);
                const float e2 = ex2((w23.x - M) * LOG2E), e3 = ex2((w23.z - M) * LOG2E);
                const float L = fmaf(e0, w01.y, e1 * w01.w) + fmaf(e2, w23.y, e3 * w23.w);
                const float o0 = fmaf(e0, v0.x, e1 * v1.x) + fmaf(e2, v2.x, e3 * v3.x);
                const float o1 = fmaf(e0, v0.y, e1 * v1.y) + fmaf(e2, v2.y, e3 * v3.y);
                st_relaxed128(g_x + dst1, __float_as_uint(o0), __float_as_uint(o1), __float_as_uint(M), __float_as_uint(L));
            }
        }
    } else {
        const int ht = tid - 128;
        bar_sync(BAR_PROBE, 224);
        const unsigned side = (smem[SM_HOME + 128] + smem[SM_HOME + 129] + smem[SM_HOME + 130]) >> 1;
        unsigned n = 0;
        while (prog[0] < SETUP_AT) {
            if (++n > SPIN_LIMIT) __trap();
            __nanosleep(1000);
        }
        st_relaxed128(g_x + near_of(X_P1 + (cta >> 1) * 8192, side) + (cta & 1) * 2048 + ht * 16, SENTINEL, SENTINEL, SENTINEL, SENTINEL);
        if (cta < NRED) {
            unsigned char* p = g_x + near_of(p2_block(cta), side) + ht * 16;
#pragma unroll
            for (int i = 0; i < 4; i++) st_relaxed128(p + (i >> 1) * P4_OFF + (i & 1) * 2048, SENTINEL, SENTINEL, SENTINEL, SENTINEL);
        } else if (cta < NRED + 16) {
            unsigned char* p = g_x + X_P3 + (cta - NRED) * 4096 + ht * 16;
            st_relaxed128(p, SENTINEL, SENTINEL, SENTINEL, SENTINEL);
            if (ht < 16) st_relaxed128(p + 2048, SENTINEL, SENTINEL, SENTINEL, SENTINEL);
        }
        if (ht == 0) st_relaxed32(&g_home[cta], side);
        __threadfence();
        bar_sync(BAR_HELP, 128);
        if (ht == 0) {
            red_add(&g_sync[32]);
            while (ld_relaxed32(&g_sync[32]) < NCTA) {
                if (++n > SPIN_LIMIT) __trap();
                __nanosleep(2000);
            }
            __threadfence();
        }
        bar_sync(BAR_HELP, 128);
        smem[SM_HOME + ht] = (unsigned char)ld_relaxed32(&g_home[ht]);
        bar_sync(BAR_HELP, 128);
        const int rd = hkv * 8 + (ht >> 4);
        reinterpret_cast<uint32_t*>(smem + SM_D1)[ht] =
            near_of(X_P1 + (rd >> 1) * 8192, smem[SM_HOME + rd]) + (rd & 1) * 2048 + r * 256 + (ht & 15) * 16;
        bar_arrive(BAR_RDY, 256);
    }

    uint32_t wad[5], dst[3];
#pragma unroll
    for (int j = 0; j < 5; j++) {
        const int nt = warp * 9 + min(2 * j + ((lane >> 3) & 1), 8);
        wad[j] = sb + SM_WO + (lane >> 4) * ROW8_PIECE + (nt >> 3) * 1024 + (lane & 7) * 128 + (((nt ^ lane) & 7) << 4);
    }
#pragma unroll
    for (int i = 0; i < 3; i++) {
        const int rd = min(warp * 9 + 4 * i + t4, NRED - 1);
        dst[i] = near_of(p2_block(rd), smem[SM_HOME + rd]) + cta * 32 + g * 4;
    }
    const uint32_t myside = smem[SM_HOME + cta];
    uint32_t src = near_of(p2_block(cta), myside) + tid * 16;
    uint32_t vad = sb + SM_ACT + (lane & 1) * 80 + (lane >> 3) * 16;
    uint32_t rd4 = sb + SM_RED4 + (warp * 16 + (lane & 8) + (lane & 1) * 4 + (lane & 2) + ((lane >> 2) & 1)) * 4;
    uint32_t wbar = bar_l + (lane & 1) * 8;
#pragma unroll 1
    for (int pass = 0;; pass++) {
#pragma unroll
        for (int j = 0; j < 5; j++) PIN(wad[j]);
        PIN(dst[0]); PIN(dst[1]); PIN(dst[2]); PIN(src); PIN(vad); PIN(rd4);
        const bool k0 = pass && !(cta & 1);
        uint32_t w0[5][2], wp[5][4], wq[5][4];
        mbar_wait_all(pass && t4 == 2 ? wbar - 8 : wbar);
#pragma unroll
        for (int j = 0; j < 5; j++) ldsm4t(wp[j], wad[j]);
        if (k0) {
#pragma unroll
            for (int j = 0; j < 5; j++) ldsm2t(w0[j][0], w0[j][1], wad[j] - ROW8_PIECE);
        }
        mbar_wait_all(wbar + 16);
#pragma unroll
        for (int j = 0; j < 5; j++) ldsm4t(wq[j], wad[j] + 2 * ROW8_PIECE);
        bar_sync(BAR_VEC, pass ? 352 : 288);
        uint32_t vb[4], v0;
        ldsm4(vb, vad + 16);
        ldsm1(v0, vad);
        float z[5][4];
#pragma unroll
        for (int j = 0; j < 5; j++) {
            z[j][0] = z[j][1] = z[j][2] = z[j][3] = 0.f;
            mma16816(z[j], wp[j][0], wp[j][1], wp[j][2], wp[j][3], vb[0], vb[1]);
        }
        if (k0) {
#pragma unroll
            for (int j = 0; j < 5; j++) mma1688(z[j], w0[j][0], w0[j][1], v0);
        }
#pragma unroll
        for (int j = 0; j < 5; j++) mma16816(z[j], wq[j][0], wq[j][1], wq[j][2], wq[j][3], vb[2], vb[3]);
#pragma unroll
        for (int i = 0; i < 2; i++) {
            const uint32_t lo = (t4 & 1) ? pack_bf16(z[2 * i][2], z[2 * i][3]) : pack_bf16(z[2 * i][0], z[2 * i][1]);
            const uint32_t hi = (t4 & 1) ? pack_bf16(z[2 * i + 1][2], z[2 * i + 1][3]) : pack_bf16(z[2 * i + 1][0], z[2 * i + 1][1]);
            st_relaxed32(g_x + dst[i], (t4 & 2) ? hi : lo);
        }
        if (t4 == 0) st_relaxed32(g_x + dst[2], pack_bf16(z[4][0], z[4][1]));
        if (cta < NRED) {
            uint4 v = make_uint4(0, 0, 0, 0);
            bool need = true;
            unsigned n = 0;
            do {
                if (++n > SPIN_LIMIT) __trap();
                ld_relaxed128_if(v, g_x + src, need);
                need = !valid4(v);
            } while (__any_sync(0xffffffffu, need));
            const bool k1 = lane & 2, k2 = lane & 4, k3 = lane & 8;
            const uint32_t u0 = k1 ? v.z : v.x, u1 = k1 ? v.w : v.y;
            const uint32_t y0 = __shfl_xor_sync(0xffffffffu, k1 ? v.x : v.z, 2), y1 = __shfl_xor_sync(0xffffffffu, k1 ? v.y : v.w, 2);
            const float s0 = bf_lo(u0) + bf_lo(y0), s1 = bf_hi(u0) + bf_hi(y0), s2 = bf_lo(u1) + bf_lo(y1), s3 = bf_hi(u1) + bf_hi(y1);
            const float a0 = (k2 ? s2 : s0) + __shfl_xor_sync(0xffffffffu, k2 ? s0 : s2, 4);
            const float a1 = (k2 ? s3 : s1) + __shfl_xor_sync(0xffffffffu, k2 ? s1 : s3, 4);
            float a = (k3 ? a1 : a0) + __shfl_xor_sync(0xffffffffu, k3 ? a0 : a1, 8);
            a += __shfl_xor_sync(0xffffffffu, a, 16);
            if (lane < 16) asm volatile("st.shared.f32 [%0], %1;" ::"r"(rd4), "f"(a) : "memory");
            __syncwarp();
            bar_arrive(BAR_SUM, 288);
        }
        if (pass) break;
        bar_sync(BAR_P2, 352);

        uint32_t fa[5][18];
        {
            const uint32_t w1a = sb + SM_W1 + (warp * 72 + (lane & 7) + 8 * (lane >> 4)) * 80 + ((lane >> 3) & 1) * 16;
            const uint32_t w3r = sb + (warp < 6 ? SM_W1 + (8 + warp) * W13_PIECE : SM_W3B + (warp - 6) * W13_PIECE) + ((lane & 7) + 8 * (lane >> 4)) * 80;
            const uint32_t w3a = w3r + ((lane >> 3) & 1) * 16;
            const uint32_t wma = ((lane >> 3) & 1) ? w3r + 64 : w1a + 64;
            mbar_wait(bar_l + 8 * (4 + warp), 0);
#pragma unroll
            for (int j = 0; j < 5; j++) {
                if (j == 2) mbar_wait(bar_l + 8 * (12 + warp), 0);
                const uint32_t base = j < 2 ? w1a + j * 32 : j < 4 ? w3a + (j - 2) * 32 : wma;
#pragma unroll
                for (int ks = 0; ks < 4; ks++) ldsm4t(*reinterpret_cast<uint32_t(*)[4]>(&fa[j][ks * 4]), base + ks * 16 * 80);
                ldsm2t(fa[j][16], fa[j][17], base + 64 * 80);
            }
        }
        const bool data = (lane & 7) < 2;
        uint32_t ha = data ? sb + SM_HS + (warp * 18 + (lane >> 3) * 2 + (lane & 1)) * 16 : sb + SM_ONES;
        uint32_t hs = data ? 128 : 0;
        uint32_t rd1 = sb + SM_RED + (warp * 80 + 2 * g) * 16 + 8 * t4;
        PIN(ha); PIN(hs); PIN(rd1);
        bar_sync(BAR_H, 320);
        uint32_t hb[12];
        ldsm4(*reinterpret_cast<uint32_t(*)[4]>(&hb[0]), ha);
        ldsm4(*reinterpret_cast<uint32_t(*)[4]>(&hb[4]), ha + hs);
        ldsm1(hb[8], ha + 2 * hs);
        float gu[5][4];
#pragma unroll
        for (int j = 0; j < 5; j++) { gu[j][0] = gu[j][1] = gu[j][2] = gu[j][3] = 0.f; }
#pragma unroll
        for (int ks = 0; ks < 4; ks++) {
#pragma unroll
            for (int j = 0; j < 5; j++)
                mma16816(gu[j], fa[j][ks * 4], fa[j][ks * 4 + 1], fa[j][ks * 4 + 2], fa[j][ks * 4 + 3], hb[2 * ks], hb[2 * ks + 1]);
        }
#pragma unroll
        for (int j = 0; j < 5; j++) mma1688(gu[j], fa[j][16], fa[j][17], hb[8]);
        if (t4 < 2) {
#pragma unroll
            for (int j = 0; j < 4; j++) {
                sts64(rd1 + ((j & 1) * 32 + (j >> 1)) * 16, gu[j][0], gu[j][1]);
                sts64(rd1 + ((j & 1) * 32 + 16 + (j >> 1)) * 16, gu[j][2], gu[j][3]);
            }
            sts64(rd1 + 64 * 16, gu[4][0], gu[4][1]);
            sts64(rd1 + 65 * 16, gu[4][2], gu[4][3]);
        }
        __syncwarp();
        bar_sync(BAR_F1, 352);
#pragma unroll
        for (int j = 0; j < 5; j++) wad[j] += SM_W2 + ROW8_PIECE - SM_WO;
        dst[0] += P4_OFF; dst[1] += P4_OFF; dst[2] += P4_OFF; src += P4_OFF;
        wbar += 8 * 21;
    }
}

typedef CUresult (*EncodeTiledFn)(CUtensorMap*, CUtensorMapDataType, cuuint32_t, void*, const cuuint64_t*, const cuuint64_t*,
                                  const cuuint32_t*, const cuuint32_t*, CUtensorMapInterleave, CUtensorMapSwizzle,
                                  CUtensorMapL2promotion, CUtensorMapFloatOOBfill);

static void encode2d(EncodeTiledFn enc, CUtensorMap* m, void* p, uint64_t cols, uint64_t rows, uint32_t bc, uint32_t br,
                     CUtensorMapSwizzle swz = CU_TENSOR_MAP_SWIZZLE_NONE) {
    cuuint64_t gd[2] = {cols, rows};
    cuuint64_t gs[1] = {cols * 2};
    cuuint32_t bx[2] = {bc, br};
    cuuint32_t es[2] = {1, 1};
    enc(m, CU_TENSOR_MAP_DATA_TYPE_BFLOAT16, 2, p, gd, gs, bx, es, CU_TENSOR_MAP_INTERLEAVE_NONE, swz,
        CU_TENSOR_MAP_L2_PROMOTION_L2_128B, CU_TENSOR_MAP_FLOAT_OOB_FILL_NONE);
}
static void encode_rows(EncodeTiledFn enc, CUtensorMap* m, void* p, uint64_t rows) {
    cuuint64_t gd[3] = {64, rows, 9};
    cuuint64_t gs[2] = {D_MODEL * 2, 128};
    cuuint32_t bx[3] = {64, 8, 9};
    cuuint32_t es[3] = {1, 1, 1};
    enc(m, CU_TENSOR_MAP_DATA_TYPE_BFLOAT16, 3, p, gd, gs, bx, es, CU_TENSOR_MAP_INTERLEAVE_NONE, CU_TENSOR_MAP_SWIZZLE_128B,
        CU_TENSOR_MAP_L2_PROMOTION_NONE, CU_TENSOR_MAP_FLOAT_OOB_FILL_NONE);
}
static void encode_kv(EncodeTiledFn enc, CUtensorMap* m, void* p) {
    cuuint64_t gd[3] = {64, (cuuint64_t)2 * HKV * SK, 2};
    cuuint64_t gs[2] = {256, 128};
    cuuint32_t bx[3] = {64, TILE_KEYS, 2};
    cuuint32_t es[3] = {1, 1, 1};
    enc(m, CU_TENSOR_MAP_DATA_TYPE_BFLOAT16, 3, p, gd, gs, bx, es, CU_TENSOR_MAP_INTERLEAVE_NONE, CU_TENSOR_MAP_SWIZZLE_128B,
        CU_TENSOR_MAP_L2_PROMOTION_NONE, CU_TENSOR_MAP_FLOAT_OOB_FILL_NONE);
}

extern "C" void kernel_launch(void* const* d_in, const int* in_sizes, int n_in, void* d_out, int out_size) {
    (void)in_sizes; (void)n_in; (void)out_size;
    static EncodeTiledFn enc = nullptr;
    if (!enc) {
        cudaDriverEntryPointQueryResult qr;
        cudaGetDriverEntryPoint("cuTensorMapEncodeTiled", (void**)&enc, cudaEnableDefault, &qr);
        cudaFuncSetAttribute(fused_decode_kernel, cudaFuncAttributeMaxDynamicSharedMemorySize, SM_TOTAL);
    }
    CUtensorMap mk, mv, mwo, mw1, mw3, mw2, mwq;
    encode2d(enc, &mwq, d_in[3], QDIM, D_MODEL, 32, 144, CU_TENSOR_MAP_SWIZZLE_64B);
    encode_kv(enc, &mk, d_in[1]);
    encode_kv(enc, &mv, d_in[2]);
    encode_rows(enc, &mwo, d_in[4], QDIM);
    encode2d(enc, &mw1, d_in[6], FF, D_MODEL, 40, 72);
    encode2d(enc, &mw3, d_in[7], FF, D_MODEL, 40, 72);
    encode_rows(enc, &mw2, d_in[8], FF);
    cudaLaunchConfig_t cfg = {};
    cfg.gridDim = dim3(NCTA); cfg.blockDim = dim3(NTHREADS); cfg.dynamicSmemBytes = SM_TOTAL; cfg.stream = cudaStreamPerThread;
    cudaLaunchAttribute at[1];
    at[0].id = cudaLaunchAttributeCooperative; at[0].val.cooperative = 1;
    cfg.attrs = at; cfg.numAttrs = 1;
    cudaLaunchKernelEx(&cfg, fused_decode_kernel, mk, mv, mwo, mw1, mw3, mw2, mwq, (const __nv_bfloat16*)d_in[0], (__nv_bfloat16*)d_out);
}
```

```cpp
#include <cuda_runtime.h>
#include <cuda_bf16.h>
#include <cuda.h>
#include <stdint.h>

namespace {

constexpr int D_MODEL = 576;
constexpr int HKV = 16;
constexpr int SK = 32768;
constexpr int QDIM = 4096;
constexpr int FF = 4608;

constexpr int NCTA = 128;
constexpr int NTHREADS = 384;
constexpr int TILE_KEYS = 64;
constexpr int NTILES = SK / 4 / TILE_KEYS;
constexpr int SLOT_BYTES = TILE_KEYS * 256;
constexpr int NSLOTS = 8;
constexpr int NKV = 2 * NTILES;
constexpr int NRED = 72;

constexpr int START_LOADS = 6, DEPTH_START = 2;
constexpr int DEPTH_MAIN = 4, DEPTH_MIN = 2;
constexpr int EARLY_W = 6;
constexpr int KV_LEFT = 2;
constexpr int DEPTH_WO = 11, DEPTH_W13 = 7, DEPTH_W2 = 6;
constexpr int SETUP_AT = 190;
constexpr int PROBES = 4;

constexpr int WQ_PIECE = 144 * 64;
constexpr int W13_PIECE = 72 * 80;
constexpr int COL_PIECE = 40 * 128;

constexpr int SM_RING = 0;
constexpr int SM_WO = SM_RING;
constexpr int SM_W3B = SM_RING + 3 * SLOT_BYTES;
constexpr int SM_W2 = SM_RING + 4 * SLOT_BYTES;
constexpr int SM_W1 = NSLOTS * SLOT_BYTES;
constexpr int SM_BAR = SM_W1 + 14 * W13_PIECE;
constexpr int SM_RED = SM_BAR + 432;
constexpr int SM_XN = SM_RED + 4096;
constexpr int XN_PITCH = 584 * 2;
constexpr int SM_ML = SM_RED + 8 * 80 * 16;
constexpr int SM_Q = SM_ML + 64;
constexpr int SM_D1 = SM_Q + 512;
constexpr int SM_ACT = SM_D1 + 512;
constexpr int SM_RED4 = SM_ACT + 192;
constexpr int SM_HS = SM_RED4 + 512;
constexpr int SM_ONES = SM_HS + 8 * 18 * 16;
constexpr int SM_PROG = SM_ONES + 16;
constexpr int SM_HOME = SM_PROG + 16;
constexpr int SM_TOTAL = SM_HOME + 144;
static_assert(SM_TOTAL <= 232448, "smem");

constexpr unsigned SENTINEL = 0xFFFFFFFFu;
constexpr float LOG2E = 1.4426950408889634f;
constexpr float SCALE = 0.08838834764831845f;
constexpr unsigned SPIN_LIMIT = 1u << 22;

}

constexpr uint32_t X_P3 = 0, X_P1 = 8 * 8192, X_P2 = 72 * 8192, X_PR = 216 * 8192, X_PQ = 232 * 8192,
                   X_SYNC = 236 * 8192, X_HOME = X_SYNC + 512, X_END = 237 * 8192;
constexpr uint32_t P4_OFF = 16384;
__device__ __forceinline__ uint32_t p2_block(int rd) { return X_P2 + (rd >> 1) * 32768 + (rd & 1) * 8192; }
static_assert(X_END <= (2u << 20), "one page");
__device__ unsigned char g_xraw[(2u << 20) + X_END];
__device__ __forceinline__ uint32_t near_of(uint32_t blk, uint32_t side) { return blk + (((__popc(blk & 0xB2000u) ^ side) & 1) << 12); }

__device__ __forceinline__ void mbar_init(uint32_t bar, uint32_t cnt) {
    asm volatile("mbarrier.init.shared::cta.b64 [%0], %1;" ::"r"(bar), "r"(cnt) : "memory");
}
__device__ __forceinline__ void mbar_expect_tx(uint32_t bar, uint32_t bytes) {
    asm volatile("mbarrier.arrive.expect_tx.shared::cta.b64 _, [%0], %1;" ::"r"(bar), "r"(bytes) : "memory");
}
__device__ __forceinline__ void mbar_arrive(uint32_t bar) {
    asm volatile("mbarrier.arrive.shared::cta.b64 _, [%0];" ::"r"(bar) : "memory");
}
__device__ __forceinline__ void mbar_wait(uint32_t bar, uint32_t parity) {
    asm volatile("{\n.reg .pred p;\n.reg .u32 n;\nmov.u32 n, 0;\n"
                 "WAIT_LOOP:\nmbarrier.try_wait.parity.shared::cta.b64 p, [%0], %1;\n@p bra WAIT_DONE;\n"
                 "add.u32 n, n, 1;\nsetp.lt.u32 p, n, 0x400000;\n@p bra WAIT_LOOP;\ntrap;\nWAIT_DONE:\n}"
                 ::"r"(bar), "r"(parity) : "memory");
}
__device__ __forceinline__ bool mbar_test(uint32_t bar, uint32_t parity) {
    uint32_t ok;
    asm volatile("{\n.reg .pred p;\nmbarrier.test_wait.parity.shared::cta.b64 p, [%1], %2;\nselp.u32 %0, 1, 0, p;\n}"
                 : "=r"(ok) : "r"(bar), "r"(parity) : "memory");
    return ok != 0;
}
__device__ __forceinline__ void mbar_wait_all(uint32_t bar) {
    uint32_t ok;
    unsigned n = 0;
    do {
        if (++n > SPIN_LIMIT) __trap();
        asm volatile("{\n.reg .pred p;\nmbarrier.try_wait.parity.shared::cta.b64 p, [%1], 0;\nselp.u32 %0, 1, 0, p;\n}"
                     : "=r"(ok) : "r"(bar) : "memory");
    } while (!__all_sync(0xffffffffu, ok));
    __syncwarp();
}
__device__ __forceinline__ void bar_sync(int id, int n) { asm volatile("bar.sync %0, %1;" ::"r"(id), "r"(n) : "memory"); }
__device__ __forceinline__ void bar_arrive(int id, int n) { asm volatile("bar.arrive %0, %1;" ::"r"(id), "r"(n) : "memory"); }

__device__ __forceinline__ void tma2d(uint32_t dst, const CUtensorMap* m, int c0, int c1, uint32_t bar) {
    asm volatile("cp.async.bulk.tensor.2d.shared::cluster.global.mbarrier::complete_tx::bytes [%0], [%1, {%3, %4}], [%2];"
                 ::"r"(dst), "l"(m), "r"(bar), "r"(c0), "r"(c1) : "memory");
}
__device__ __forceinline__ void tma3d_hint(uint32_t dst, const CUtensorMap* m, int c1, uint32_t bar, uint64_t pol) {
    asm volatile("cp.async.bulk.tensor.3d.shared::cluster.global.mbarrier::complete_tx::bytes.L2::cache_hint [%0], [%1, {0, %3, 0}], [%2], %4;"
                 ::"r"(dst), "l"(m), "r"(bar), "r"(c1), "l"(pol) : "memory");
}
__device__ __forceinline__ void ldsm4(uint32_t (&r)[4], uint32_t a) {
    asm volatile("ldmatrix.sync.aligned.m8n8.x4.shared.b16 {%0,%1,%2,%3}, [%4];"
                 : "=r"(r[0]), "=r"(r[1]), "=r"(r[2]), "=r"(r[3]) : "r"(a) : "memory");
}
__device__ __forceinline__ void ldsm4t(uint32_t (&r)[4], uint32_t a) {
    asm volatile("ldmatrix.sync.aligned.m8n8.x4.trans.shared.b16 {%0,%1,%2,%3}, [%4];"
                 : "=r"(r[0]), "=r"(r[1]), "=r"(r[2]), "=r"(r[3]) : "r"(a) : "memory");
}
__device__ __forceinline__ void ldsm2t(uint32_t& r0, uint32_t& r1, uint32_t a) {
    asm volatile("ldmatrix.sync.aligned.m8n8.x2.trans.shared.b16 {%0,%1}, [%2];" : "=r"(r0), "=r"(r1) : "r"(a) : "memory");
}
__device__ __forceinline__ void ldsm1t(uint32_t& r0, uint32_t a) {
    asm volatile("ldmatrix.sync.aligned.m8n8.x1.trans.shared.b16 {%0}, [%1];" : "=r"(r0) : "r"(a) : "memory");
}
__device__ __forceinline__ void ldsm1(uint32_t& r0, uint32_t a) {
    asm volatile("ldmatrix.sync.aligned.m8n8.x1.shared.b16 {%0}, [%1];" : "=r"(r0) : "r"(a) : "memory");
}
__device__ __forceinline__ void mma16816(float (&c)[4], uint32_t a0, uint32_t a1, uint32_t a2, uint32_t a3, uint32_t b0, uint32_t b1) {
    asm("mma.sync.aligned.m16n8k16.row.col.f32.bf16.bf16.f32 {%0,%1,%2,%3}, {%4,%5,%6,%7}, {%8,%9}, {%0,%1,%2,%3};"
                 : "+f"(c[0]), "+f"(c[1]), "+f"(c[2]), "+f"(c[3]) : "r"(a0), "r"(a1), "r"(a2), "r"(a3), "r"(b0), "r"(b1));
}
__device__ __forceinline__ float4 lds128(uint32_t a) {
    float4 v;
    asm volatile("ld.shared.v4.f32 {%0,%1,%2,%3}, [%4];" : "=f"(v.x), "=f"(v.y), "=f"(v.z), "=f"(v.w) : "r"(a) : "memory");
    return v;
}
__device__ __forceinline__ void sts64(uint32_t a, float x, float y) {
    asm volatile("st.shared.v2.f32 [%0], {%1,%2};" ::"r"(a), "f"(x), "f"(y) : "memory");
}
__device__ __forceinline__ void mma1688(float (&c)[4], uint32_t a0, uint32_t a1, uint32_t b0) {
    asm("mma.sync.aligned.m16n8k8.row.col.f32.bf16.bf16.f32 {%0,%1,%2,%3}, {%4,%5}, {%6}, {%0,%1,%2,%3};"
                 : "+f"(c[0]), "+f"(c[1]), "+f"(c[2]), "+f"(c[3]) : "r"(a0), "r"(a1), "r"(b0));
}
__device__ __forceinline__ uint32_t movm(uint32_t a) {
    uint32_t d;
    asm volatile("movmatrix.sync.aligned.m8n8.trans.b16 %0, %1;" : "=r"(d) : "r"(a));
    return d;
}
__device__ __forceinline__ uint32_t pack_bf16(float lo, float hi) {
    uint32_t d;
    asm("cvt.rn.bf16x2.f32 %0, %1, %2;" : "=r"(d) : "f"(hi), "f"(lo));
    return d;
}
__device__ __forceinline__ float bf_lo(uint32_t v) { return __uint_as_float(v << 16); }
__device__ __forceinline__ float bf_hi(uint32_t v) { return __uint_as_float(v & 0xFFFF0000u); }
__device__ __forceinline__ float bfr(float x) { return __uint_as_float(pack_bf16(0.f, x)); }
__device__ __forceinline__ float ex2(float x) { float y; asm("ex2.approx.ftz.f32 %0, %1;" : "=f"(y) : "f"(x)); return y; }
__device__ __forceinline__ float rcp(float x) { float y; asm("rcp.approx.ftz.f32 %0, %1;" : "=f"(y) : "f"(x)); return y; }

__device__ __forceinline__ void ld_relaxed128_if(uint4& v, const void* p, bool need) {
    asm volatile("{\n.reg .pred q;\n.reg .b128 t;\n.reg .b64 lo, hi;\nsetp.ne.u32 q, %5, 0;\nmov.b64 lo, {%0, %1};\nmov.b64 hi, {%2, %3};\n"
                 "mov.b128 t, {lo, hi};\n@q ld.relaxed.gpu.global.b128 t, [%4];\nmov.b128 {lo, hi}, t;\n"
                 "mov.b64 {%0, %1}, lo;\nmov.b64 {%2, %3}, hi;\n}"
                 : "+r"(v.x), "+r"(v.y), "+r"(v.z), "+r"(v.w) : "l"(p), "r"((unsigned)need) : "memory");
}
__device__ __forceinline__ void st_relaxed128(void* p, uint32_t x, uint32_t y, uint32_t z, uint32_t w) {
    asm volatile("{\n.reg .b128 t;\n.reg .b64 lo, hi;\nmov.b64 lo, {%1, %2};\nmov.b64 hi, {%3, %4};\nmov.b128 t, {lo, hi};\n"
                 "st.relaxed.gpu.global.b128 [%0], t;\n}"
                 ::"l"(p), "r"(x), "r"(y), "r"(z), "r"(w) : "memory");
}
__device__ __forceinline__ uint2 ld_relaxed64(const void* p) {
    uint2 v;
    asm volatile("{\n.reg .b64 t;\nld.relaxed.gpu.global.b64 t, [%2];\nmov.b64 {%0, %1}, t;\n}" : "=r"(v.x), "=r"(v.y) : "l"(p) : "memory");
    return v;
}
__device__ __forceinline__ void st_relaxed64(void* p, uint32_t x, uint32_t y) {
    asm volatile("{\n.reg .b64 t;\nmov.b64 t, {%1, %2};\nst.relaxed.gpu.global.b64 [%0], t;\n}" ::"l"(p), "r"(x), "r"(y) : "memory");
}
__device__ __forceinline__ unsigned ld_relaxed32(const void* p) {
    unsigned v;
    asm volatile("ld.relaxed.gpu.global.u32 %0, [%1];" : "=r"(v) : "l"(p) : "memory");
    return v;
}
__device__ __forceinline__ void st_relaxed32(void* p, unsigned v) {
    asm volatile("st.relaxed.gpu.global.u32 [%0], %1;" ::"l"(p), "r"(v) : "memory");
}
__device__ __forceinline__ void red_add(unsigned* p) {
    asm volatile("red.relaxed.gpu.global.add.u32 [%0], 1;" ::"l"(p) : "memory");
}
__device__ __forceinline__ bool valid4(const uint4& v) {
    return v.x != SENTINEL && v.y != SENTINEL && v.z != SENTINEL && v.w != SENTINEL;
}

__device__ __forceinline__ unsigned near_page(unsigned* p) {
#pragma unroll
    for (int i = 0; i < 4; i++) st_relaxed128(p + (i >> 1) * 1024 + (i & 1) * 4, 0, 0, 0, 0);
    unsigned best0 = 0xffffffffu, best1 = 0xffffffffu;
#pragma unroll 1
    for (int i = 0; i < 2 * PROBES + 1; i++) {
        unsigned v, t0, t1;
        asm volatile("mov.u32 %0, %%clock;" : "=r"(t0) :: "memory");
        asm volatile("atom.relaxed.gpu.global.add.u32 %0, [%1], 1;" : "=r"(v) : "l"(p + ((i & 1) << 10)) : "memory");
        asm volatile("{\n.reg .pred p;\nsetp.ne.u32 p, %1, 0x5a5a5a5a;\nmov.u32 %0, 0;\n@p mov.u32 %0, %%clock;\n}" : "=r"(t1) : "r"(v) : "memory");
        if (i & 1) best1 = min(best1, t1 - t0); else best0 = min(best0, t1 - t0);
    }
    return best1 < best0;
}

__device__ __forceinline__ uint32_t finish_sum(uint32_t a, uint32_t res) {
    float2 c[8];
#pragma unroll
    for (int i = 0; i < 8; i++) asm volatile("ld.shared.v2.f32 {%0,%1}, [%2];" : "=f"(c[i].x), "=f"(c[i].y) : "r"(a + i * 64) : "memory");
    const uint32_t t = pack_bf16(((c[0].x + c[1].x) + (c[2].x + c[3].x)) + ((c[4].x + c[5].x) + (c[6].x + c[7].x)),
                                 ((c[0].y + c[1].y) + (c[2].y + c[3].y)) + ((c[4].y + c[5].y) + (c[6].y + c[7].y)));
    return pack_bf16(bf_lo(res) + bf_lo(t), bf_hi(res) + bf_hi(t));
}

enum { BAR_ALL = 1, BAR_MAIN = 2, BAR_HELP = 3, BAR_RDY = 4, BAR_INIT = 5, BAR_PROBE = 6, BAR_F1 = 7, BAR_VEC = 8,
       BAR_SUM = 9, BAR_OWN = 10, BAR_H = 11, BAR_P2 = 12, BAR_AUX = 13 };
#define PIN(v) asm volatile("" : "+r"(v))

__global__ void __launch_bounds__(NTHREADS, 1)
fused_decode_kernel(const __grid_constant__ CUtensorMap map_k, const __grid_constant__ CUtensorMap map_v,
                    const __grid_constant__ CUtensorMap map_wo, const __grid_constant__ CUtensorMap map_w1,
                    const __grid_constant__ CUtensorMap map_w3, const __grid_constant__ CUtensorMap map_w2,
                    const __grid_constant__ CUtensorMap map_w2o, const __grid_constant__ CUtensorMap map_wq,
                    const __nv_bfloat16* __restrict__ x,
                    __nv_bfloat16* __restrict__ out) {
    extern __shared__ __align__(1024) unsigned char smem[];
    const uint32_t sb = (uint32_t)__cvta_generic_to_shared(smem);
    const int tid = threadIdx.x, lane = tid & 31;
    if (tid == 0) {
        const uint32_t bw = sb + SM_BAR + 128;
#pragma unroll
        for (int p = 0; p < 4; p++) mbar_init(bw + 8 * p, 1);
#pragma unroll
        for (int p = 0; p < 4; p++) {
            mbar_expect_tx(bw + 8 * p, WQ_PIECE);
            tma2d(sb + SM_W1 + p * WQ_PIECE, &map_wq, blockIdx.x * 32, p * 144, bw + 8 * p);
        }
    }
    if (tid < 32) { __syncwarp(); bar_arrive(BAR_INIT, 96); }
    const int warp = __shfl_sync(0xffffffffu, tid >> 5, 0);
    const int cta = blockIdx.x;
    const int hkv = cta >> 3, r = cta & 7;
    const uint32_t bar_full = sb + SM_BAR, bar_empty = bar_full + 64, bar_w = bar_full + 128,
                   bar_l = bar_full + 160;
    volatile int* const prog = reinterpret_cast<volatile int*>(smem + SM_PROG);
    float* const red = reinterpret_cast<float*>(smem + SM_RED);
    unsigned char* const g_x = reinterpret_cast<unsigned char*>((reinterpret_cast<uintptr_t>(g_xraw) + 0x1FFFFF) & ~(uintptr_t)0x1FFFFF);
    unsigned* const sync = reinterpret_cast<unsigned*>(g_x + X_SYNC);
    unsigned* const home = reinterpret_cast<unsigned*>(g_x + X_HOME);
    uint2 (*const pq)[HKV][128] = reinterpret_cast<uint2 (*)[HKV][128]>(g_x + X_PQ);
    const int g = lane >> 2, t4 = lane & 3;

    if (warp == 8) {
        bar_sync(BAR_INIT, 96);
        const int f0 = (cta >> 1) * 72 + (cta & 1) * 32;
        if (lane == 0) {
            uint64_t pol;
            asm volatile("createpolicy.fractional.L2::evict_first.b64 %0, 1.0;" : "=l"(pol));
            const int row0 = ((r >> 2) * HKV + hkv) * SK + (r & 3) * (2 * TILE_KEYS);
#pragma unroll 1
            for (int i = 0; i < NKV; i++) {
                const int slot = i & (NSLOTS - 1);
                if (i >= NSLOTS) mbar_wait(bar_empty + 8 * slot, ((i >> 3) - 1) & 1);
                const int j = i - (i < START_LOADS ? DEPTH_START : (int)prog[1]);
                if (j >= 0) mbar_wait(bar_full + 8 * (j & 7), (j >> 3) & 1);
                else if (i == 1) mbar_wait(bar_w + 16, 0);
                prog[0] = j + 1;
                const int row = row0 + ((i >> 2) ^ ((hkv & 1) << 3)) * (8 * TILE_KEYS) + ((i >> 1) & 1) * TILE_KEYS;
                mbar_expect_tx(bar_full + 8 * slot, SLOT_BYTES);
                tma3d_hint(sb + SM_RING + slot * SLOT_BYTES, (i & 1) ? &map_v : &map_k, row, bar_full + 8 * slot, pol);
                if (i >= 32 && i < 32 + EARLY_W) {
                    mbar_expect_tx(bar_l + 72 + 8 * slot, W13_PIECE);
                    tma2d(sb + SM_W1 + slot * W13_PIECE, &map_w1, f0, slot * 72, bar_l + 72 + 8 * slot);
                }
                if (i == NKV - 32) {
                    asm volatile("prefetch.tensormap [%0];" ::"l"(&map_wo) : "memory");
                    asm volatile("prefetch.tensormap [%0];" ::"l"(&map_w3) : "memory");
                    asm volatile("prefetch.tensormap [%0];" ::"l"((cta & 1) ? &map_w2o : &map_w2) : "memory");
                }
            }
            prog[0] = NKV;
        }
        __syncwarp();
        {
            const int q = lane, p = q < 9 ? q : q + EARLY_W, odd = cta & 1;
            const uint32_t bar = bar_l + 8 * p;
            const CUtensorMap* map = p < 9 ? &map_wo : p < 17 ? &map_w1 : p < 25 ? &map_w3 : odd ? &map_w2o : &map_w2;
            const uint32_t dst = sb + (p < 9 ? SM_WO + p * COL_PIECE + 1024 : p < 23 ? SM_W1 + (p - 9) * W13_PIECE
                                     : p < 25 ? SM_W3B + (p - 23) * W13_PIECE : SM_W2 + (p - 25) * COL_PIECE + odd * 1024);
            const int c0 = p < 9 ? p * 64 : p < 25 ? f0 : (p - 25) * 64;
            const int c1 = p < 9 ? cta * 32 : p < 25 ? ((p - 9) & 7) * 72 : f0 + odd * 8;
            const int d = p < 25 ? max(DEPTH_W13, DEPTH_WO - max(q - 11, 0)) : DEPTH_W2;
            const int qa = q - d;
            const uint32_t ga = qa >= 0 ? bar_l + 8 * (qa < 9 ? qa : qa + EARLY_W) : bar_full + 8 * min(7, 7 - KV_LEFT + (q >> 2));
            const uint32_t gb = bar_empty + 8 * (p >= 25 ? 6 : 3);
            bool todo = p < 34;
            if (todo) mbar_expect_tx(bar, p < 9 ? 4096 : p < 25 ? W13_PIECE : COL_PIECE - odd * 1024);
            unsigned n = 0;
            while (__any_sync(0xffffffffu, todo)) {
                if (++n > (SPIN_LIMIT << 2)) __trap();
                if (todo && (prog[2] || mbar_test(ga, qa >= 0 ? 0 : 1)) && mbar_test(gb, 1)) {
                    tma2d(dst, map, c0, c1, bar);
                    todo = false;
                }
            }
        }
        return;
    }

    if (warp > 8) {
        if (warp == 9) {
            if (lane == 0) {
#pragma unroll 1
                for (int i = 0; i < 8; i++) { mbar_init(bar_full + 8 * i, 1); mbar_init(bar_empty + 8 * i, 4); }
                prog[0] = 0; prog[1] = DEPTH_MAIN; prog[2] = 0;
#pragma unroll 2
                for (int i = 0; i < 34; i++) mbar_init(bar_l + 8 * i, 1);
                *reinterpret_cast<uint4*>(smem + SM_ONES) = make_uint4(0x3F803F80u, 0x3F803F80u, 0x3F803F80u, 0x3F803F80u);
            }
            __syncwarp();
            bar_arrive(BAR_INIT, 96);
            bar_arrive(0, 288);
        }
        if (lane == 0) {
            const uint32_t blk = X_PR + (cta & 15) * 8192;
            smem[SM_HOME + 128 + warp - 9] = (near_page(reinterpret_cast<unsigned*>(g_x + blk + (cta >> 4) * 512 + (warp - 9) * 128)) ^ __popc(blk & 0xB2000u)) & 1;
        }
        __syncwarp();
        bar_sync(BAR_PROBE, 224);
        uint32_t res = 0, rs4 = sb + SM_RED4 + (lane & 7) * 8;
        const unsigned side = (smem[SM_HOME + 128] + smem[SM_HOME + 129] + smem[SM_HOME + 130]) >> 1;
        if (warp == 9) {
            if (lane == 0) {
                int last = 0, cur;
                unsigned n = 0;
                do {
                    if (++n > SPIN_LIMIT) __trap();
                    __nanosleep(700);
                    cur = prog[0];
                    const int tot = (int)atomicAdd(&sync[64], (unsigned)(cur - last));
                    last = cur;
                    const int lead = prog[(unsigned)tot >> 31] * NCTA - tot;
                    prog[1] = max(DEPTH_MIN, min(NSLOTS, DEPTH_MAIN + (((cur < NKV - 12 ? 31 : 191) - lead) >> 8)));
                } while (cur < NKV - 1);
            }
            __syncwarp();
        } else if (warp == 10) {
            const unsigned char* pp = g_x + near_of(X_P1 + (cta >> 1) * 8192, side) + (cta & 1) * 2048 + (lane >> 4) * 1024 + (lane & 15) * 16;
            uint32_t oa = sb + SM_ACT + (lane >> 4) * 80 + 16 + (lane & 15) * 4;
            PIN(oa);
            uint4 v[4];
#pragma unroll
            for (int i = 0; i < 4; i++) v[i] = make_uint4(0, 0, 0, SENTINEL);
            unsigned n = 0;
            bar_sync(BAR_OWN, 160);
            do {
                if (++n > SPIN_LIMIT) __trap();
#pragma unroll
                for (int i = 0; i < 4; i++) ld_relaxed128_if(v[i], pp + i * 256, v[i].w == SENTINEL);
            } while (__any_sync(0xffffffffu, v[0].w == SENTINEL || v[1].w == SENTINEL || v[2].w == SENTINEL || v[3].w == SENTINEL));
            const float W = fmaxf(fmaxf(__uint_as_float(v[0].z), __uint_as_float(v[1].z)), fmaxf(__uint_as_float(v[2].z), __uint_as_float(v[3].z)));
            float e[4];
#pragma unroll
            for (int i = 0; i < 4; i++) e[i] = ex2((__uint_as_float(v[i].z) - W) * LOG2E);
            const float inv = rcp(fmaf(e[0], __uint_as_float(v[0].w), e[1] * __uint_as_float(v[1].w)) + fmaf(e[2], __uint_as_float(v[2].w), e[3] * __uint_as_float(v[3].w)));
            const float o0 = fmaf(e[0], __uint_as_float(v[0].x), e[1] * __uint_as_float(v[1].x)) + fmaf(e[2], __uint_as_float(v[2].x), e[3] * __uint_as_float(v[3].x));
            const float o1 = fmaf(e[0], __uint_as_float(v[0].y), e[1] * __uint_as_float(v[1].y)) + fmaf(e[2], __uint_as_float(v[2].y), e[3] * __uint_as_float(v[3].y));
            asm volatile("st.shared.u32 [%0], %1;" ::"r"(oa), "r"(pack_bf16(o0 * inv, o1 * inv)) : "memory");
            __syncwarp();
            bar_arrive(BAR_VEC, 288);
        } else if (cta < NRED) {
            res = ld_relaxed32(reinterpret_cast<const uint32_t*>(x + (g & 1) * D_MODEL + cta * 8) + t4);
            unsigned char* hp = g_x + X_P3 + (lane >> 3) * 16384 + cta * 32 + (lane & 7) * 4;
            PIN(res); PIN(rs4);
            bar_sync(BAR_SUM, 288);
            res = finish_sum(rs4, res);
#pragma unroll
            for (int i = 0; i < 4; i++) st_relaxed32(hp + i * 4096, res);
        }
        if (warp < 11) {
            const uint32_t off = ((warp - 9) * 72 + lane) * 16;
            const unsigned char* hp = g_x + near_of(X_P3 + (cta & 7) * 8192, side) + off;
            uint4 u[3];
            bool need[3];
#pragma unroll
            for (int i = 0; i < 3; i++) { u[i] = make_uint4(0, 0, 0, 0); need[i] = lane < 24; }
            bar_sync(BAR_P2, 352);
            unsigned n = 0;
            do {
                if (++n > SPIN_LIMIT) __trap();
#pragma unroll
                for (int i = 0; i < 3; i++) ld_relaxed128_if(u[i], hp + i * 384, need[i]);
#pragma unroll
                for (int i = 0; i < 3; i++) need[i] = !valid4(u[i]);
                if (lane < 24 && !(need[0] && need[1] && need[2])) prog[2] = 1;
            } while (__any_sync(0xffffffffu, need[0] || need[1] || need[2]));
            if (lane < 24) {
#pragma unroll
                for (int i = 0; i < 3; i++) *reinterpret_cast<uint4*>(smem + SM_HS + off + i * 384) = u[i];
            }
            __syncwarp();
            bar_arrive(BAR_H, 320);
            const float c0 = __shfl_sync(0xffffffffu, bf_lo(u[0].x), lane & 1), cl = lane < 24 ? c0 : 0.f;
            float sm = 0.f, sq = 0.f;
#pragma unroll
            for (int i = 0; i < 3; i++) {
                const uint32_t w[4] = {u[i].x, u[i].y, u[i].z, u[i].w};
                float s1 = 0.f, s2 = 0.f;
#pragma unroll
                for (int k = 0; k < 4; k++) {
                    const float lo = bf_lo(w[k]) - cl, hi = bf_hi(w[k]) - cl;
                    s1 += lo + hi;
                    s2 = fmaf(lo, lo, fmaf(hi, hi, s2));
                }
                sm += s1; sq += s2;
            }
#pragma unroll
            for (int o = 2; o < 32; o <<= 1) {
                sm += __shfl_xor_sync(0xffffffffu, sm, o);
                sq += __shfl_xor_sync(0xffffffffu, sq, o);
            }
            if (lane < 2) *reinterpret_cast<float2*>(smem + SM_ML + lane * 16 + (warp - 9) * 8) =
                make_float2(fmaf(sm, 1.f / 288, c0), fmaf(sm * (-1.f / 288), sm, sq));
        } else {
            bar_arrive(BAR_P2, 352);
        }
        bar_sync(BAR_AUX, 96);
        const int at = tid - 288, bb = at & 1;
        uint32_t ra = sb + SM_RED + min(at, 79) * 16;
        uint32_t wa = sb + SM_ACT + bb * 80 + (at >> 1) * 2;
        const float4 st = lds128(sb + SM_ML + bb * 16);
        const float mean = 0.5f * (st.x + st.z);
        const float var = fmaxf(fmaf(144.f * (st.x - st.z), st.x - st.z, st.y + st.w) * (1.f / D_MODEL), 0.f);
        float mb = bfr(mean), sd, isd;
        asm("sqrt.approx.ftz.f32 %0, %1;" : "=f"(sd) : "f"(bfr(bfr(var) + 1e-5f)));
        asm volatile("rcp.approx.ftz.f32 %0, %1;" : "=f"(isd) : "f"(bfr(sd)));
        bar_sync(BAR_F1, 352);
        float4 u[8];
#pragma unroll
        for (int wv = 0; wv < 8; wv++) u[wv] = lds128(ra + wv * 80 * 16);
#pragma unroll
        for (int d = 4; d; d >>= 1) {
#pragma unroll
            for (int i = 0; i < d; i++) { u[i].x += u[i + d].x; u[i].y += u[i + d].y; u[i].z += u[i + d].z; }
        }
        const float v0 = u[0].x, v1 = u[0].y, cs = u[0].z;
        const float ov = __shfl_xor_sync(0xffffffffu, bb ? v0 : v1, 1), ocs = __shfl_xor_sync(0xffffffffu, cs, 1);
        const float gt = bfr(fmaf(-mb, bb ? ocs : cs, bb ? ov : v0) * isd);
        const float up = bfr(fmaf(-mb, bb ? cs : ocs, bb ? v1 : ov) * isd);
        const float act = bfr(gt * rcp(1.f + ex2(-gt * LOG2E))) * up;
        if (at < 80) asm volatile("st.shared.u16 [%0], %1;" ::"r"(wa), "h"((unsigned short)pack_bf16(act, 0.f)) : "memory");
        bar_arrive(BAR_VEC, 352);
        if (warp == 11 && cta < NRED) {
            uint32_t* op = reinterpret_cast<uint32_t*>(out + (g & 1) * D_MODEL + cta * 8) + t4;
            bar_sync(BAR_SUM, 288);
            res = finish_sum(rs4, res);
            if (lane < 8) *op = res;
            if (cta == 0 && lane == 0) {
                red_add(&sync[0]);
                st_relaxed32(&sync[32], 0);
                st_relaxed32(&sync[64], 0);
            }
        }
        return;
    }

    unsigned tag;
    {
        const uint32_t* xp = reinterpret_cast<const uint32_t*>(x + (warp >> 2) * D_MODEL);
        uint32_t xu[9], xo[3];
#pragma unroll
        for (int i = 0; i < 9; i++) xu[i] = __ldg(xp + lane + 32 * i);
        tag = ld_relaxed32(&sync[0]) + 1;
        const int wq4 = warp & 3;
        xo[0] = wq4 == 0 ? xu[0] : wq4 == 1 ? xu[1] : wq4 == 2 ? xu[2] : xu[3];
        xo[1] = wq4 == 0 ? xu[4] : wq4 == 1 ? xu[5] : wq4 == 2 ? xu[6] : xu[7];
        xo[2] = xu[8];
        float s = 0.f;
#pragma unroll
        for (int i = 0; i < 9; i++) s += bf_lo(xu[i]) + bf_hi(xu[i]);
#pragma unroll
        for (int o = 16; o; o >>= 1) s += __shfl_xor_sync(0xffffffffu, s, o);
        const float mean = __fdiv_rn(s, (float)D_MODEL);
        float q2 = 0.f;
#pragma unroll
        for (int i = 0; i < 9; i++) {
            const float d0 = bf_lo(xu[i]) - mean, d1 = bf_hi(xu[i]) - mean;
            q2 = fmaf(d0, d0, fmaf(d1, d1, q2));
        }
#pragma unroll
        for (int o = 16; o; o >>= 1) q2 += __shfl_xor_sync(0xffffffffu, q2, o);
        const float mb = bfr(mean);
        const float sd = bfr(__fsqrt_rn(bfr(bfr(__fdiv_rn(q2, (float)D_MODEL)) + 1e-5f)));
#pragma unroll 1
        for (int i = 0; i < 3; i++) {
            const uint32_t u = i == 0 ? xo[0] : i == 1 ? xo[1] : xo[2];
            const int wi = i < 2 ? 4 * i + wq4 : 8;
            *reinterpret_cast<uint32_t*>(smem + SM_XN + (warp >> 2) * XN_PITCH + 4 * (lane + 32 * wi)) =
                pack_bf16(__fdiv_rn(bfr(bf_lo(u) - mb), sd), __fdiv_rn(bfr(bf_hi(u) - mb), sd));
        }
        bar_sync(0, 288);
        uint32_t xb[12];
        const uint32_t xa = sb + SM_XN + (lane & 1) * XN_PITCH + (warp * 72 + 8 * (lane >> 3)) * 2;
        ldsm4(*reinterpret_cast<uint32_t(*)[4]>(&xb[0]), xa);
        ldsm4(*reinterpret_cast<uint32_t(*)[4]>(&xb[4]), xa + 64);
        ldsm1(xb[8], xa + 128);
        mbar_wait(bar_w + 8 * (warp >> 1), 0);
        const uint32_t wa = sb + SM_W1 + (warp * 72 + (lane & 7) + 8 * (lane >> 4)) * 64;
        float qa[2][4];
#pragma unroll
        for (int j = 0; j < 2; j++) {
            const uint32_t ad = wa + (((2 * j + ((lane >> 3) & 1)) ^ ((lane >> 1) & 3)) << 4);
            qa[j][0] = qa[j][1] = qa[j][2] = qa[j][3] = 0.f;
#pragma unroll
            for (int ks = 0; ks < 4; ks++) {
                uint32_t a4[4];
                ldsm4t(a4, ad + ks * 16 * 64);
                mma16816(qa[j], a4[0], a4[1], a4[2], a4[3], xb[2 * ks], xb[2 * ks + 1]);
            }
            uint32_t a0, a1;
            ldsm2t(a0, a1, ad + 64 * 64);
            mma1688(qa[j], a0, a1, xb[8]);
        }
#pragma unroll
        for (int j = 0; j < 2; j++) {
            const float lo = (t4 & 1) ? qa[j][1] : qa[j][0], hi = (t4 & 1) ? qa[j][3] : qa[j][2];
            red[warp * 64 + (t4 & 1) * 32 + 16 * j + g + 8 * (t4 >> 1)] = (t4 & 2) ? hi : lo;
        }
        bar_sync(BAR_ALL, 256);
        if (warp == 0) {
            float s0 = 0.f, s1 = 0.f;
#pragma unroll
            for (int wv = 0; wv < 8; wv++) {
                const float2 v = *reinterpret_cast<const float2*>(red + wv * 64 + lane * 2);
                s0 += v.x; s1 += v.y;
            }
            st_relaxed64(&pq[lane >> 4][hkv][r * 16 + (lane & 15)], pack_bf16(s0, s1), tag);
        }
    }

    if (warp < 4) {
        float* const ml = reinterpret_cast<float*>(smem + SM_ML);
        uint32_t* const qs = reinterpret_cast<uint32_t*>(smem + SM_Q);
        {
            uint2 v;
            unsigned n = 0;
            do {
                if (++n > SPIN_LIMIT) __trap();
                __nanosleep(1000);
                v = ld_relaxed64(&pq[r >> 2][hkv][tid]);
            } while (__any_sync(0xffffffffu, v.y != tag));
            qs[tid] = v.x;
            bar_sync(BAR_MAIN, 128);
        }
        uint32_t koff[4], voff[4];
        {
            const int l7 = lane & 7;
            const uint32_t kb = (warp * 16 + l7 + 8 * ((lane >> 3) & 1)) * 128;
            const uint32_t vb = (warp * 16 + l7 + 8 * (lane >> 4)) * 128;
#pragma unroll
            for (int i = 0; i < 4; i++) {
                koff[i] = sb + SM_RING + kb + (((2 * i + (lane >> 4)) ^ l7) << 4);
                voff[i] = sb + SM_RING + SLOT_BYTES + vb + (((2 * i + ((lane >> 3) & 1)) ^ l7) << 4);
            }
        }
        {
            uint32_t qb[8][2];
#pragma unroll
            for (int ks = 0; ks < 8; ks++) {
                qb[ks][0] = qs[(g & 1) * 64 + ks * 8 + t4];
                qb[ks][1] = qs[(g & 1) * 64 + ks * 8 + 4 + t4];
            }
            float o[8][4];
#pragma unroll
            for (int i = 0; i < 8; i++) { o[i][0] = o[i][1] = o[i][2] = o[i][3] = 0.f; }
            float m0 = -INFINITY, m1 = -INFINITY, l0 = 0.f, l1 = 0.f;
#pragma unroll 1
            for (int t = 0; t < NTILES; t++) {
                const int slot = (2 * t) & (NSLOTS - 1);
                const uint32_t ph = (t >> 2) & 1;
                const uint32_t so = slot * SLOT_BYTES;
                mbar_wait(bar_full + 8 * slot, ph);
                uint32_t a[8][4];
#pragma unroll
                for (int ks = 0; ks < 8; ks++) ldsm4(a[ks], koff[ks & 3] + so + (ks >> 2) * 8192);
                __syncwarp();
                if (lane == 0) mbar_arrive(bar_empty + 8 * slot);
                float c[4] = {0.f, 0.f, 0.f, 0.f}, c2[4] = {0.f, 0.f, 0.f, 0.f};
#pragma unroll
                for (int ks = 0; ks < 8; ks += 2) {
                    mma16816(c, a[ks][0], a[ks][1], a[ks][2], a[ks][3], qb[ks][0], qb[ks][1]);
                    mma16816(c2, a[ks + 1][0], a[ks + 1][1], a[ks + 1][2], a[ks + 1][3], qb[ks + 1][0], qb[ks + 1][1]);
                }
                uint32_t u0 = pack_bf16(c[0] + c2[0], c[1] + c2[1]), u1 = pack_bf16(c[2] + c2[2], c[3] + c2[3]);
                u0 = pack_bf16(bf_lo(u0) * SCALE, bf_hi(u0) * SCALE);
                u1 = pack_bf16(bf_lo(u1) * SCALE, bf_hi(u1) * SCALE);
                const float s0 = bf_lo(u0), s1 = bf_hi(u0), s2 = bf_lo(u1), s3 = bf_hi(u1);
                float x0 = fmaxf(s0, s2), x1 = fmaxf(s1, s3);
                if (__any_sync(0xffffffffu, x0 > m0 || x1 > m1)) {
#pragma unroll
                    for (int of = 4; of < 32; of <<= 1) {
                        x0 = fmaxf(x0, __shfl_xor_sync(0xffffffffu, x0, of));
                        x1 = fmaxf(x1, __shfl_xor_sync(0xffffffffu, x1, of));
                    }
                    x0 = fmaxf(m0, x0); x1 = fmaxf(m1, x1);
                    const float al0 = ex2((m0 - x0) * LOG2E), al1 = ex2((m1 - x1) * LOG2E);
                    m0 = x0; m1 = x1;
                    l0 *= al0; l1 *= al1;
#pragma unroll
                    for (int i = 0; i < 8; i++) { o[i][0] *= al0; o[i][1] *= al1; o[i][2] *= al0; o[i][3] *= al1; }
                }
                const float p0 = ex2((s0 - m0) * LOG2E), p1 = ex2((s1 - m1) * LOG2E);
                const float p2 = ex2((s2 - m0) * LOG2E), p3 = ex2((s3 - m1) * LOG2E);
                l0 += p0 + p2; l1 += p1 + p3;
                const uint32_t pb0 = movm(pack_bf16(p0, p1)), pb1 = movm(pack_bf16(p2, p3));
                mbar_wait(bar_full + 8 * slot + 8, ph);
#pragma unroll
                for (int mt = 0; mt < 8; mt++) ldsm4t(a[mt], voff[mt & 3] + so + (mt >> 2) * 8192);
                __syncwarp();
                if (lane == 0) mbar_arrive(bar_empty + 8 * slot + 8);
#pragma unroll
                for (int mt = 0; mt < 8; mt++) mma16816(o[mt], a[mt][0], a[mt][1], a[mt][2], a[mt][3], pb0, pb1);
            }
#pragma unroll
            for (int of = 4; of < 32; of <<= 1) {
                l0 += __shfl_xor_sync(0xffffffffu, l0, of);
                l1 += __shfl_xor_sync(0xffffffffu, l1, of);
            }
            if (lane < 2) *reinterpret_cast<float2*>(ml + lane * 8 + warp * 2) = lane ? make_float2(m1, l1) : make_float2(m0, l0);
            {
                float* dst = red + warp * 288 + (t4 & 1) * 144 + g + 8 * (t4 >> 1);
#pragma unroll
                for (int mt = 0; mt < 8; mt++) {
                    const float lo = (t4 & 1) ? o[mt][1] : o[mt][0], hi = (t4 & 1) ? o[mt][3] : o[mt][2];
                    dst[16 * mt] = (t4 & 2) ? hi : lo;
                }
            }
            bar_sync(BAR_RDY, 256);
            bar_arrive(BAR_OWN, 160);
            {
                const int h = tid >> 6, j = tid & 63;
                const float4 w01 = *reinterpret_cast<const float4*>(ml + h * 8), w23 = *reinterpret_cast<const float4*>(ml + h * 8 + 4);
                const float* op = red + h * 144 + 2 * j;
                const float2 v0 = *reinterpret_cast<const float2*>(op), v1 = *reinterpret_cast<const float2*>(op + 288);
                const float2 v2 = *reinterpret_cast<const float2*>(op + 576), v3 = *reinterpret_cast<const float2*>(op + 864);
                const uint32_t dst1 = reinterpret_cast<const uint32_t*>(smem + SM_D1)[tid];
                const float M = fmaxf(fmaxf(w01.x, w01.z), fmaxf(w23.x, w23.z));
                const float e0 = ex2((w01.x - M) * LOG2E), e1 = ex2((w01.z - M) * LOG2E);
                const float e2 = ex2((w23.x - M) * LOG2E), e3 = ex2((w23.z - M) * LOG2E);
                const float L = fmaf(e0, w01.y, e1 * w01.w) + fmaf(e2, w23.y, e3 * w23.w);
                const float o0 = fmaf(e0, v0.x, e1 * v1.x) + fmaf(e2, v2.x, e3 * v3.x);
                const float o1 = fmaf(e0, v0.y, e1 * v1.y) + fmaf(e2, v2.y, e3 * v3.y);
                st_relaxed128(g_x + dst1, __float_as_uint(o0), __float_as_uint(o1), __float_as_uint(M), __float_as_uint(L));
            }
        }
    } else {
        const int ht = tid - 128;
        bar_sync(BAR_PROBE, 224);
        const unsigned side = (smem[SM_HOME + 128] + smem[SM_HOME + 129] + smem[SM_HOME + 130]) >> 1;
        unsigned n = 0;
        while (prog[0] < SETUP_AT) {
            if (++n > SPIN_LIMIT) __trap();
            __nanosleep(1000);
        }
        st_relaxed128(g_x + near_of(X_P1 + (cta >> 1) * 8192, side) + (cta & 1) * 2048 + ht * 16, SENTINEL, SENTINEL, SENTINEL, SENTINEL);
        if (cta < NRED) {
            unsigned char* p = g_x + near_of(p2_block(cta), side) + ht * 16;
#pragma unroll
            for (int i = 0; i < 4; i++) st_relaxed128(p + (i >> 1) * P4_OFF + (i & 1) * 2048, SENTINEL, SENTINEL, SENTINEL, SENTINEL);
        } else if (cta < NRED + 16) {
            unsigned char* p = g_x + X_P3 + (cta - NRED) * 4096 + ht * 16;
            st_relaxed128(p, SENTINEL, SENTINEL, SENTINEL, SENTINEL);
            if (ht < 16) st_relaxed128(p + 2048, SENTINEL, SENTINEL, SENTINEL, SENTINEL);
        }
        if (ht == 0) st_relaxed32(&home[cta], side);
        __threadfence();
        bar_sync(BAR_HELP, 128);
        if (ht == 0) {
            red_add(&sync[32]);
            while (ld_relaxed32(&sync[32]) < NCTA) {
                if (++n > SPIN_LIMIT) __trap();
                __nanosleep(2000);
            }
            __threadfence();
        }
        bar_sync(BAR_HELP, 128);
        smem[SM_HOME + ht] = (unsigned char)ld_relaxed32(&home[ht]);
        bar_sync(BAR_HELP, 128);
        const int rd = hkv * 8 + (ht >> 4);
        reinterpret_cast<uint32_t*>(smem + SM_D1)[ht] =
            near_of(X_P1 + (rd >> 1) * 8192, smem[SM_HOME + rd]) + (rd & 1) * 2048 + r * 256 + (ht & 15) * 16;
        bar_arrive(BAR_RDY, 256);
    }

    uint32_t wad[5], dst[3];
#pragma unroll
    for (int j = 0; j < 5; j++) {
        const int nt = warp * 9 + min(2 * j + ((lane >> 3) & 1), 8);
        wad[j] = sb + SM_WO + (1 + (j == 4 ? (lane >> 3) & 1 : lane >> 4)) * 1024 + (nt >> 3) * COL_PIECE + (lane & 7) * 128 + (((nt ^ lane) & 7) << 4);
    }
#pragma unroll
    for (int i = 0; i < 3; i++) {
        const int rd = min(warp * 9 + 4 * i + t4, NRED - 1);
        dst[i] = near_of(p2_block(rd), smem[SM_HOME + rd]) + cta * 32 + g * 4;
    }
    const uint32_t myside = smem[SM_HOME + cta];
    uint32_t src = near_of(p2_block(cta), myside) + tid * 16;
    uint32_t vad = sb + SM_ACT + (lane & 1) * 80 + (lane >> 3) * 16;
    uint32_t rd4 = sb + SM_RED4 + (warp * 16 + (lane & 8) + (lane & 1) * 4 + (lane & 2) + ((lane >> 2) & 1)) * 4;
    uint32_t wbar = bar_l + (warp + (lane & 1)) * 8;
#pragma unroll 1
    for (int pass = 0;; pass++) {
#pragma unroll
        for (int j = 0; j < 5; j++) PIN(wad[j]);
        PIN(dst[0]); PIN(dst[1]); PIN(dst[2]); PIN(src); PIN(vad); PIN(rd4);
        const bool k0 = pass && !(cta & 1);
        uint32_t w0[5][2] = {}, wp[5][4] = {}, wq[5][4] = {};
        auto load_w = [&]() {
#pragma unroll
            for (int j = 0; j < 4; j++) ldsm4t(wp[j], wad[j]);
            ldsm2t(wp[4][0], wp[4][2], wad[4]);
            if (k0) {
#pragma unroll
                for (int j = 0; j < 4; j++) ldsm2t(w0[j][0], w0[j][1], wad[j] - 1024);
                ldsm1t(w0[4][0], wad[4] - 1024);
            }
#pragma unroll
            for (int j = 0; j < 4; j++) ldsm4t(wq[j], wad[j] + 2048);
            ldsm2t(wq[4][0], wq[4][2], wad[4] + 2048);
        };
        if (!pass) mbar_wait_all(wbar);
        const bool have = __all_sync(0xffffffffu, mbar_test(wbar, 0));
        __syncwarp();
        if (have) load_w();
        bar_sync(BAR_VEC, pass ? 352 : 288);
        uint32_t vb[4], v0;
        ldsm4(vb, vad + 16);
        ldsm1(v0, vad);
        if (!have) { mbar_wait_all(wbar); load_w(); }
        float z[5][4];
#pragma unroll
        for (int j = 0; j < 5; j++) {
            z[j][0] = z[j][1] = z[j][2] = z[j][3] = 0.f;
            mma16816(z[j], wp[j][0], wp[j][1], wp[j][2], wp[j][3], vb[0], vb[1]);
        }
        if (k0) {
#pragma unroll
            for (int j = 0; j < 5; j++) mma1688(z[j], w0[j][0], w0[j][1], v0);
        }
#pragma unroll
        for (int j = 0; j < 5; j++) mma16816(z[j], wq[j][0], wq[j][1], wq[j][2], wq[j][3], vb[2], vb[3]);
#pragma unroll
        for (int i = 0; i < 2; i++) {
            const uint32_t lo = (t4 & 1) ? pack_bf16(z[2 * i][2], z[2 * i][3]) : pack_bf16(z[2 * i][0], z[2 * i][1]);
            const uint32_t hi = (t4 & 1) ? pack_bf16(z[2 * i + 1][2], z[2 * i + 1][3]) : pack_bf16(z[2 * i + 1][0], z[2 * i + 1][1]);
            st_relaxed32(g_x + dst[i], (t4 & 2) ? hi : lo);
        }
        if (t4 == 0) st_relaxed32(g_x + dst[2], pack_bf16(z[4][0], z[4][1]));
        if (cta < NRED) {
            uint4 v = make_uint4(0, 0, 0, 0);
            bool need = true;
            unsigned n = 0;
            do {
                if (++n > SPIN_LIMIT) __trap();
                ld_relaxed128_if(v, g_x + src, need);
                need = !valid4(v);
            } while (__any_sync(0xffffffffu, need));
            const bool k1 = lane & 2, k2 = lane & 4, k3 = lane & 8;
            const uint32_t u0 = k1 ? v.z : v.x, u1 = k1 ? v.w : v.y;
            const uint32_t y0 = __shfl_xor_sync(0xffffffffu, k1 ? v.x : v.z, 2), y1 = __shfl_xor_sync(0xffffffffu, k1 ? v.y : v.w, 2);
            const float s0 = bf_lo(u0) + bf_lo(y0), s1 = bf_hi(u0) + bf_hi(y0), s2 = bf_lo(u1) + bf_lo(y1), s3 = bf_hi(u1) + bf_hi(y1);
            const float a0 = (k2 ? s2 : s0) + __shfl_xor_sync(0xffffffffu, k2 ? s0 : s2, 4);
            const float a1 = (k2 ? s3 : s1) + __shfl_xor_sync(0xffffffffu, k2 ? s1 : s3, 4);
            float a = (k3 ? a1 : a0) + __shfl_xor_sync(0xffffffffu, k3 ? a0 : a1, 8);
            a += __shfl_xor_sync(0xffffffffu, a, 16);
            if (lane < 16) asm volatile("st.shared.f32 [%0], %1;" ::"r"(rd4), "f"(a) : "memory");
            __syncwarp();
            bar_arrive(BAR_SUM, 288);
        }
        if (pass) break;
        bar_sync(BAR_P2, 352);

        uint32_t fa[5][18];
        {
            const uint32_t w1a = sb + SM_W1 + (warp * 72 + (lane & 7) + 8 * (lane >> 4)) * 80 + ((lane >> 3) & 1) * 16;
            const uint32_t w3r = sb + (warp < 6 ? SM_W1 + (8 + warp) * W13_PIECE : SM_W3B + (warp - 6) * W13_PIECE) + ((lane & 7) + 8 * (lane >> 4)) * 80;
            const uint32_t w3a = w3r + ((lane >> 3) & 1) * 16;
            const uint32_t wma = ((lane >> 3) & 1) ? w3r + 64 : w1a + 64;
            mbar_wait(bar_l + 8 * (9 + warp), 0);
#pragma unroll
            for (int j = 0; j < 5; j++) {
                if (j == 2) mbar_wait(bar_l + 8 * (17 + warp), 0);
                const uint32_t base = j < 2 ? w1a + j * 32 : j < 4 ? w3a + (j - 2) * 32 : wma;
#pragma unroll
                for (int ks = 0; ks < 4; ks++) ldsm4t(*reinterpret_cast<uint32_t(*)[4]>(&fa[j][ks * 4]), base + ks * 16 * 80);
                ldsm2t(fa[j][16], fa[j][17], base + 64 * 80);
            }
        }
        const bool data = !(lane & 2);
        uint32_t ha = data ? sb + SM_HS + (warp * 18 + (lane >> 3) * 2 + (lane & 1)) * 16 : sb + SM_ONES;
        uint32_t hs = data ? 128 : 0;
        uint32_t rd1 = sb + SM_RED + (warp * 80 + 2 * g) * 16 + 8 * (t4 & 1);
        PIN(ha); PIN(hs); PIN(rd1);
        bar_sync(BAR_H, 320);
        uint32_t hb[12];
        ldsm4(*reinterpret_cast<uint32_t(*)[4]>(&hb[0]), ha);
        ldsm4(*reinterpret_cast<uint32_t(*)[4]>(&hb[4]), ha + hs);
        ldsm1(hb[8], ha + 2 * hs);
        float gu[5][4];
#pragma unroll
        for (int j = 0; j < 5; j++) { gu[j][0] = gu[j][1] = gu[j][2] = gu[j][3] = 0.f; }
#pragma unroll
        for (int ks = 0; ks < 4; ks++) {
#pragma unroll
            for (int j = 0; j < 5; j++)
                mma16816(gu[j], fa[j][ks * 4], fa[j][ks * 4 + 1], fa[j][ks * 4 + 2], fa[j][ks * 4 + 3], hb[2 * ks], hb[2 * ks + 1]);
        }
#pragma unroll
        for (int j = 0; j < 5; j++) mma1688(gu[j], fa[j][16], fa[j][17], hb[8]);
        {
            const bool hi = t4 & 2;
            const uint32_t ra = rd1 + (hi ? 256 : 0);
#pragma unroll
            for (int j = 0; j < 4; j++) sts64(ra + ((j & 1) * 32 + (j >> 1)) * 16, hi ? gu[j][2] : gu[j][0], hi ? gu[j][3] : gu[j][1]);
            sts64(rd1 + 64 * 16 + (hi ? 16 : 0), hi ? gu[4][2] : gu[4][0], hi ? gu[4][3] : gu[4][1]);
        }
        __syncwarp();
        bar_sync(BAR_F1, 352);
#pragma unroll
        for (int j = 0; j < 5; j++) wad[j] += SM_W2 - SM_WO;
        dst[0] += P4_OFF; dst[1] += P4_OFF; dst[2] += P4_OFF; src += P4_OFF;
        wbar += 8 * 25;
    }
}

typedef CUresult (*EncodeTiledFn)(CUtensorMap*, CUtensorMapDataType, cuuint32_t, void*, const cuuint64_t*, const cuuint64_t*,
                                  const cuuint32_t*, const cuuint32_t*, CUtensorMapInterleave, CUtensorMapSwizzle,
                                  CUtensorMapL2promotion, CUtensorMapFloatOOBfill);

static void encode2d(EncodeTiledFn enc, CUtensorMap* m, void* p, uint64_t cols, uint64_t rows, uint32_t bc, uint32_t br,
                     CUtensorMapSwizzle swz = CU_TENSOR_MAP_SWIZZLE_NONE) {
    cuuint64_t gd[2] = {cols, rows};
    cuuint64_t gs[1] = {cols * 2};
    cuuint32_t bx[2] = {bc, br};
    cuuint32_t es[2] = {1, 1};
    enc(m, CU_TENSOR_MAP_DATA_TYPE_BFLOAT16, 2, p, gd, gs, bx, es, CU_TENSOR_MAP_INTERLEAVE_NONE, swz,
        CU_TENSOR_MAP_L2_PROMOTION_L2_128B, CU_TENSOR_MAP_FLOAT_OOB_FILL_NONE);
}
static void encode_kv(EncodeTiledFn enc, CUtensorMap* m, void* p) {
    cuuint64_t gd[3] = {64, (cuuint64_t)2 * HKV * SK, 2};
    cuuint64_t gs[2] = {256, 128};
    cuuint32_t bx[3] = {64, TILE_KEYS, 2};
    cuuint32_t es[3] = {1, 1, 1};
    enc(m, CU_TENSOR_MAP_DATA_TYPE_BFLOAT16, 3, p, gd, gs, bx, es, CU_TENSOR_MAP_INTERLEAVE_NONE, CU_TENSOR_MAP_SWIZZLE_128B,
        CU_TENSOR_MAP_L2_PROMOTION_NONE, CU_TENSOR_MAP_FLOAT_OOB_FILL_NONE);
}

extern "C" void kernel_launch(void* const* d_in, const int* in_sizes, int n_in, void* d_out, int out_size) {
    (void)in_sizes; (void)n_in; (void)out_size;
    static EncodeTiledFn enc = nullptr;
    if (!enc) {
        cudaDriverEntryPointQueryResult qr;
        cudaGetDriverEntryPoint("cuTensorMapEncodeTiled", (void**)&enc, cudaEnableDefault, &qr);
        cudaFuncSetAttribute(fused_decode_kernel, cudaFuncAttributeMaxDynamicSharedMemorySize, SM_TOTAL);
    }
    CUtensorMap mk, mv, mwo, mw1, mw3, mw2, mw2o, mwq;
    encode2d(enc, &mwq, d_in[3], QDIM, D_MODEL, 32, 144, CU_TENSOR_MAP_SWIZZLE_64B);
    encode_kv(enc, &mk, d_in[1]);
    encode_kv(enc, &mv, d_in[2]);
    encode2d(enc, &mwo, d_in[4], D_MODEL, QDIM, 64, 32, CU_TENSOR_MAP_SWIZZLE_128B);
    encode2d(enc, &mw1, d_in[6], FF, D_MODEL, 40, 72);
    encode2d(enc, &mw3, d_in[7], FF, D_MODEL, 40, 72);
    encode2d(enc, &mw2, d_in[8], D_MODEL, FF, 64, 40, CU_TENSOR_MAP_SWIZZLE_128B);
    encode2d(enc, &mw2o, d_in[8], D_MODEL, FF, 64, 32, CU_TENSOR_MAP_SWIZZLE_128B);
    cudaLaunchConfig_t cfg = {};
    cfg.gridDim = dim3(NCTA); cfg.blockDim = dim3(NTHREADS); cfg.dynamicSmemBytes = SM_TOTAL; cfg.stream = cudaStreamPerThread;
    cudaLaunchAttribute at[1];
    at[0].id = cudaLaunchAttributeCooperative; at[0].val.cooperative = 1;
    cfg.attrs = at; cfg.numAttrs = 1;
    cudaLaunchKernelEx(&cfg, fused_decode_kernel, mk, mv, mwo, mw1, mw3, mw2, mw2o, mwq, (const __nv_bfloat16*)d_in[0], (__nv_bfloat16*)d_out);
}
```
